```python
import torch

def _softmax(x, axis=-1):
    return torch.softmax(x, dim=axis)
def _gelu(x):
    return torch.nn.functional.gelu(x, approximate="tanh")
def _silu(x):
    return torch.nn.functional.silu(x)
def _sigmoid(x):
    return torch.sigmoid(x)
def _layernorm(x, axis=-1, eps=1e-5):
    m = x.mean(dim=axis, keepdim=True)
    v = x.var(dim=axis, keepdim=True, unbiased=False)
    return (x - m) / torch.sqrt(v + eps)
def _scatter_add(tgt, idx, src, axis=0):
    return tgt.clone().index_add_(axis, idx, src)
def _segment_sum(src, seg, n):
    out = torch.zeros((n,) + src.shape[1:], dtype=src.dtype)
    return out.index_add_(0, seg, src)
def _pad(x, pw):
    flat = tuple(v for pair in reversed(pw) for v in pair)
    return torch.nn.functional.pad(x, flat)

kernel_name = 'gated_mix__spectral_gfnet__ssm_conv_s5__prompt'

def setup_inputs():

    _w = (lambda a: (lambda t: t.to(torch.bfloat16) if t.is_floating_point() else t)(torch.as_tensor(a)))
    def _A_setup():
        B, S, D = 1, 2048, 1024
        Df = D // 2 + 1
        return {
            "x": _w((lambda *s: torch.randn(*s, dtype=torch.bfloat16) * 0.05)(B, S, D)),
            "w_r": _w((lambda *s: torch.randn(*s, dtype=torch.bfloat16) * 0.8)(S, Df) * 0.02),
            "w_i": _w((lambda *s: torch.randn(*s, dtype=torch.bfloat16) * 0.8)(S, Df) * 0.02),
        }
    _A_in = _A_setup()

    def _B_setup():
        B, S, D = 1, 2048, 1024
        P = D
        Lambda_re = -0.5 * (lambda _x: torch.exp(torch.as_tensor(_x)))((lambda *s: torch.randn(*s, dtype=torch.bfloat16) * 0.2)(P))
        Lambda_im = (lambda *s: torch.randn(*s, dtype=torch.bfloat16) * 0.4)(P) * 1.0
        B_re = (lambda *s: torch.randn(*s, dtype=torch.bfloat16) * 0.2)(P, D) * (D ** -0.5)
        B_im = (lambda *s: torch.randn(*s, dtype=torch.bfloat16) * 0.2)(P, D) * (D ** -0.5)
        C_re = (lambda *s: torch.randn(*s, dtype=torch.bfloat16) * 0.2)(D, P) * (P ** -0.5)
        C_im = (lambda *s: torch.randn(*s, dtype=torch.bfloat16) * 0.2)(D, P) * (P ** -0.5)
        log_dt = (lambda *s: torch.randn(*s, dtype=torch.bfloat16) * 0.2)(P) * 0.3 - 2.0
        Dskip = (lambda *s: torch.randn(*s, dtype=torch.bfloat16) * 0.05)(D)
        return {
            "x": _w((lambda *s: torch.randn(*s, dtype=torch.bfloat16) * 0.05)(B, S, D)),
            "Lambda_re": _w(Lambda_re),
            "Lambda_im": _w(Lambda_im),
            "B_re": _w(B_re),
            "B_im": _w(B_im),
            "C_re": _w(C_re),
            "C_im": _w(C_im),
            "log_dt": _w(log_dt),
            "Dskip": _w(Dskip),
        }
    _B_in = _B_setup()

    return {
        "A_x": _A_in["x"],
        "A_w_r": _A_in["w_r"],
        "A_w_i": _A_in["w_i"],
        "B_x": _B_in["x"],
        "B_Lambda_re": _B_in["Lambda_re"],
        "B_Lambda_im": _B_in["Lambda_im"],
        "B_B_re": _B_in["B_re"],
        "B_B_im": _B_in["B_im"],
        "B_C_re": _B_in["C_re"],
        "B_C_im": _B_in["C_im"],
        "B_log_dt": _B_in["log_dt"],
        "B_Dskip": _B_in["Dskip"],
        "gate_w": _w((lambda *s: torch.randn(*s, dtype=torch.bfloat16) * 0.05)(1024) * 16.0),
    }

def reference(A_x, A_w_r, A_w_i, B_x, B_Lambda_re, B_Lambda_im, B_B_re, B_B_im, B_C_re, B_C_im, B_log_dt, B_Dskip, gate_w):
    def _A_ref(x, w_r, w_i):
        B, S, D = x.shape
        X = (lambda x, axes=(-2,-1): torch.fft.rfft2(x.float(), dim=axes))(x, axes=(-2, -1))
        W = w_r + 1j * w_i
        X = X * W
        y = (lambda x, s, axes=(-2,-1): torch.fft.irfft2(x, s=s, dim=axes).to(torch.bfloat16))(X, (S, D), axes=(-2, -1))
        return y

    def _B_ref(x, Lambda_re, Lambda_im, B_re, B_im, C_re, C_im, log_dt, Dskip):
        Bsz, L, H = x.shape
        Lam = Lambda_re + 1j * Lambda_im
        Bmat = B_re + 1j * B_im
        Cmat = C_re + 1j * C_im
        dt = torch.exp(log_dt)
        Lam_bar = torch.exp(dt * Lam)
        B_bar = ((Lam_bar - 1.0) / Lam)[:, None] * Bmat
        Bu = torch.einsum("bld,pd->blp", x + 0j, B_bar)
        h = torch.zeros_like(Bu[:, 0, :])
        hs = []
        for t in range(L):
            h = Lam_bar[None, :] * h + Bu[:, t, :]
            hs.append(h)
        hseq = torch.stack(hs, 1)
        y = 2.0 * torch.einsum("blp,dp->bld", hseq, Cmat).real + x * Dskip[None, None, :]
        return y

    x = A_x
    g = _sigmoid((x * gate_w).sum(-1, keepdims=True))
    a = _A_ref(x, A_w_r, A_w_i)
    b = _B_ref(x, B_Lambda_re, B_Lambda_im, B_B_re, B_B_im, B_C_re, B_C_im, B_log_dt, B_Dskip)
    return g * a + (1 - g) * b
```

```cpp
#include <cuda_runtime.h>
#include <cuda_bf16.h>
#include <cuda.h>
#include <stdint.h>

#define ABL 0
#define S_LEN 2048
#define D_DIM 1024
#define P_DIM 1024

namespace ct {
constexpr double PI = 3.14159265358979323846264338327950288;
constexpr double tsin(double x) { double term = x, sum = x; for (int i = 1; i < 12; i++) { term *= -x * x / ((2 * i) * (2 * i + 1)); sum += term; } return sum; }
constexpr double tcos(double x) { double term = 1, sum = 1; for (int i = 1; i < 12; i++) { term *= -x * x / ((2 * i - 1) * (2 * i)); sum += term; } return sum; }
struct CosTab { double v[513]; };
constexpr CosTab make_cos() {
    CosTab t{};
    for (int m = 0; m <= 512; m++) t.v[m] = m == 512 ? 0.0 : (m <= 256 ? tcos(2 * PI * m / 2048.0) : tsin(2 * PI * (512 - m) / 2048.0));
    return t;
}
constexpr CosTab COS = make_cos();
constexpr double cos2048(int m) {
    m &= 2047;
    if (m > 1024) m = 2048 - m;
    if (m > 512) return -COS.v[1024 - m];
    return COS.v[m];
}
constexpr double sin2048(int m) { return cos2048(m - 512); }
constexpr unsigned short bf16bits(double v) {
    if (v == 0.0) return 0;
    unsigned short s = 0;
    if (v < 0) { s = 0x8000; v = -v; }
    int e = 0;
    while (v >= 2.0) { v *= 0.5; e++; }
    while (v < 1.0) { v *= 2.0; e--; }
    double r = v * 128.0;
    int ri = (int)r;
    double fr = r - ri;
    if (fr > 0.5 || (fr == 0.5 && (ri & 1))) ri++;
    if (ri == 256) { ri = 128; e++; }
    return (unsigned short)(s | ((e + 127) << 7) | (ri - 128));
}
constexpr int kmaj(int row, int k, int sbo) { return ((row >> 3) * sbo + (k >> 3) * 128 + (row & 7) * 16 + (k & 7) * 2) >> 1; }
constexpr double rot(int ro, int ri, int a) { return ro == ri ? cos2048(a) : (ro == 0 ? sin2048(a) : -sin2048(a)); }
constexpr int bin(int n) { return (n & 8) | ((n & 3) << 1) | ((n >> 2) & 1); }
constexpr int bout(int n) { return ((n & 2) << 2) | ((n >> 1) & 6) | (n & 1); }
struct Half {
    unsigned short m4[4096];
    unsigned short b16i[1024];
    unsigned short tw[2][128][8];
};
struct Img { unsigned short b16f[1024]; Half h[2]; float cs[16][128][2]; };
constexpr Img make_img() {
    Img t{};
    for (int n = 0; n < 32; n++) for (int k = 0; k < 32; k++) t.b16f[kmaj(n, k, 512)] = bf16bits(rot(((n >> 4) ^ (n >> 3)) & 1, k >> 4, bin(k & 15) * (n & 15) * 128));
    for (int r = 0; r < 16; r++) for (int j = 0; j < 128; j++) { t.cs[r][j][0] = (float)cos2048(16 * j + r); t.cs[r][j][1] = (float)sin2048(16 * j + r); }
    for (int ke = 0; ke < 2; ke++) {
        Half& h = t.h[ke];
        for (int n = 0; n < 32; n++) for (int k = 0; k < 32; k++) h.b16i[kmaj(n, k, 512)] = bf16bits(rot(n >> 4, ((k >> 4) ^ (k >> 3)) & 1, -bout(n & 15) * (k & 15) * 128));
        for (int m = 0; m < 64; m++) for (int k = 0; k < 64; k++) {
            int a = 4 * (m >> 3) + (m & 3), ro = (m >> 2) & 1, kx = 8 * (k >> 4) + (k & 7), ri = (k >> 3) & 1;
            h.m4[kmaj(m, k, 1024)] = bf16bits(rot(ro, ri, -a * (ke + 2 * kx) * 32));
        }
        for (int tid = 0; tid < 128; tid++) {
            int kap = ke + 2 * (tid >> 2), q = tid & 3;
            for (int hb = 0; hb < 2; hb++) for (int e = 0; e < 2; e++) {
                int n = 8 * hb + 2 * q + e;
                h.tw[0][tid][4 * hb + e] = bf16bits(cos2048(2 * bin(n) * kap));  h.tw[0][tid][4 * hb + 2 + e] = bf16bits(-sin2048(2 * bin(n) * kap));
                h.tw[1][tid][4 * hb + e] = bf16bits(cos2048(2 * bout(n) * kap)); h.tw[1][tid][4 * hb + 2 + e] = bf16bits(sin2048(2 * bout(n) * kap));
            }
        }
    }
    return t;
}
}
__device__ __align__(128) const ct::Img g_img = ct::make_img();

#define RING 4
#define STGB 32768
#define R0 (4 * 32768)
#define R1 (5 * 32768)
#define R2 (6 * 32768)
#define B16F_OFF (7 * 32768)
#define BAR_OFF (B16F_OFF + 2048)
#define GATE_OFF (BAR_OFF + 256)
#define DSK_OFF (GATE_OFF + 512)
#define TOT_SMEM (DSK_OFF + 256)
#define NCTA 132
#define X2_IMG 36864

__device__ __align__(1024) uint4 g_X1[130 * 2048];
__device__ __align__(1024) uint4 g_X2[128 * X2_IMG / 16];
__device__ __align__(128) float g_gp[256 * 128];
__device__ __align__(1024) uint4 g_h[16 * 32 * 1024];
__device__ __align__(128) unsigned long long g_agg[16 * P_DIM];
__device__ __align__(128) unsigned int g_cnt[7 * 32];
#define g_ticket g_cnt[0]
#define g_cnt1 g_cnt[32]
#define g_cnt2 g_cnt[64]
#define g_cnth(i) g_cnt[96 + 32 * (i)]

#define DBG_STAMP(slot)
#define DBG_RAW(slot, v)

__device__ __forceinline__ float bf16r(float v) { return __bfloat162float(__float2bfloat16_rn(v)); }
__device__ __forceinline__ float2 cmul(float2 a, float2 b) { return make_float2(a.x * b.x - a.y * b.y, a.x * b.y + a.y * b.x); }
__device__ __forceinline__ float2 cfma(float2 a, float2 b, float2 c) {
    float re = fmaf(a.x, b.x, c.x); re = fmaf(-a.y, b.y, re);
    float im = fmaf(a.x, b.y, c.y); im = fmaf(a.y, b.x, im);
    return make_float2(re, im);
}
__device__ __forceinline__ uint32_t smem_u32(const void* p) { return (uint32_t)__cvta_generic_to_shared(p); }
__device__ __forceinline__ void bar_sync_n(int id, int n) { asm volatile("bar.sync %0, %1;" :: "r"(id), "r"(n) : "memory"); }
__device__ __forceinline__ void bar_arrive_n(int id, int n) { asm volatile("bar.arrive %0, %1;" :: "r"(id), "r"(n) : "memory"); }
__device__ __forceinline__ uint32_t pack2(float lo, float hi) { uint32_t r; asm("cvt.rn.bf16x2.f32 %0, %1, %2;" : "=r"(r) : "f"(hi), "f"(lo)); return r; }
__device__ __forceinline__ uint64_t mkd(uint32_t b16, uint32_t off, uint32_t lbo, uint32_t sbo, uint32_t swz = 0) {
    uint64_t d;
    asm("mov.b64 %0, {%1, %2};" : "=l"(d) : "r"(b16 + ((off >> 4) + ((lbo >> 4) << 16))), "r"((sbo >> 4) | (swz << 30)));
    return d;
}
__device__ __forceinline__ uint32_t to16(uint32_t saddr) { return (saddr & 0x3FFFF) >> 4; }
__device__ __forceinline__ void wgmma_fence() { asm volatile("wgmma.fence.sync.aligned;" ::: "memory"); }
__device__ __forceinline__ void wgmma_commit() { asm volatile("wgmma.commit_group.sync.aligned;" ::: "memory"); }
template <int N> __device__ __forceinline__ void wgmma_wait() { asm volatile("wgmma.wait_group.sync.aligned %0;" :: "n"(N) : "memory"); }
__device__ __forceinline__ void fence_async() { asm volatile("fence.proxy.async.shared::cta;" ::: "memory"); }
template <int N> __device__ __forceinline__ void reg_fence(float* d) {
    #pragma unroll
    for (int i = 0; i < N; i++) asm volatile("" : "+f"(d[i]) :: "memory");
}
#define X16(c, d, o) c(d[o]),c(d[o+1]),c(d[o+2]),c(d[o+3]),c(d[o+4]),c(d[o+5]),c(d[o+6]),c(d[o+7]),c(d[o+8]),c(d[o+9]),c(d[o+10]),c(d[o+11]),c(d[o+12]),c(d[o+13]),c(d[o+14]),c(d[o+15])
#define RW(x) "+f"(x)
#define WO(x) "=f"(x)
#define R64(d) X16(RW, d, 0), X16(RW, d, 16), X16(RW, d, 32), X16(RW, d, 48)
#define W64(d) X16(WO, d, 0), X16(WO, d, 16), X16(WO, d, 32), X16(WO, d, 48)
#define R32(d) X16(RW, d, 0), X16(RW, d, 16)
#define W32(d) X16(WO, d, 0), X16(WO, d, 16)
#define R16(d) X16(RW, d, 0)
#define WO16(d) X16(WO, d, 0)
#define L64 "{%0,%1,%2,%3,%4,%5,%6,%7,%8,%9,%10,%11,%12,%13,%14,%15,%16,%17,%18,%19,%20,%21,%22,%23,%24,%25,%26,%27,%28,%29,%30,%31," \
        "%32,%33,%34,%35,%36,%37,%38,%39,%40,%41,%42,%43,%44,%45,%46,%47,%48,%49,%50,%51,%52,%53,%54,%55,%56,%57,%58,%59,%60,%61,%62,%63}"
#define L32 "{%0,%1,%2,%3,%4,%5,%6,%7,%8,%9,%10,%11,%12,%13,%14,%15,%16,%17,%18,%19,%20,%21,%22,%23,%24,%25,%26,%27,%28,%29,%30,%31}"
#define L16 "{%0,%1,%2,%3,%4,%5,%6,%7,%8,%9,%10,%11,%12,%13,%14,%15}"

template <int TA, int TB> __device__ __forceinline__ void ss128(float* d, uint64_t a, uint64_t b) {
    asm volatile("wgmma.mma_async.sync.aligned.m64n128k16.f32.bf16.bf16 " L64 ", %64, %65, 1, 1, 1, %66, %67;\n" : R64(d) : "l"(a), "l"(b), "n"(TA), "n"(TB));
}
template <int TA, int TB> __device__ __forceinline__ void ss128_p(float* d, uint64_t a, uint64_t b, int acc) {
    asm volatile("{\n.reg .pred p;\nsetp.ne.s32 p, %68, 0;\nwgmma.mma_async.sync.aligned.m64n128k16.f32.bf16.bf16 " L64 ", %64, %65, p, 1, 1, %66, %67;\n}\n" : R64(d) : "l"(a), "l"(b), "n"(TA), "n"(TB), "r"(acc));
}
template <int TA, int TB> __device__ __forceinline__ void ss128_z(float* d, uint64_t a, uint64_t b) {
    asm volatile("wgmma.mma_async.sync.aligned.m64n128k16.f32.bf16.bf16 " L64 ", %64, %65, 0, 1, 1, %66, %67;\n" : W64(d) : "l"(a), "l"(b), "n"(TA), "n"(TB));
}
__device__ __forceinline__ void rs64(float* d, uint4 a, uint64_t b) {
    asm volatile("wgmma.mma_async.sync.aligned.m64n64k16.f32.bf16.bf16 " L32 ", {%32,%33,%34,%35}, %36, 1, 1, 1, 0;\n" : R32(d) : "r"(a.x), "r"(a.y), "r"(a.z), "r"(a.w), "l"(b));
}
__device__ __forceinline__ void rs64_z(float* d, uint4 a, uint64_t b) {
    asm volatile("wgmma.mma_async.sync.aligned.m64n64k16.f32.bf16.bf16 " L32 ", {%32,%33,%34,%35}, %36, 0, 1, 1, 0;\n" : W32(d) : "r"(a.x), "r"(a.y), "r"(a.z), "r"(a.w), "l"(b));
}
__device__ __forceinline__ void rs32(float* d, uint32_t a0, uint32_t a1, uint32_t a2, uint32_t a3, uint64_t b) {
    asm volatile("wgmma.mma_async.sync.aligned.m64n32k16.f32.bf16.bf16 " L16 ", {%16,%17,%18,%19}, %20, 1, 1, 1, 0;\n"
        : R16(d) : "r"(a0), "r"(a1), "r"(a2), "r"(a3), "l"(b));
}
__device__ __forceinline__ void rs32_z(float* d, uint32_t a0, uint32_t a1, uint32_t a2, uint32_t a3, uint64_t b) {
    asm volatile("wgmma.mma_async.sync.aligned.m64n32k16.f32.bf16.bf16 " L16 ", {%16,%17,%18,%19}, %20, 0, 1, 1, 0;\n"
        : WO16(d) : "r"(a0), "r"(a1), "r"(a2), "r"(a3), "l"(b));
}
__device__ __forceinline__ void stsm_x4(uint32_t addr, uint32_t r0, uint32_t r1, uint32_t r2, uint32_t r3) {
    asm volatile("stmatrix.sync.aligned.m8n8.x4.shared.b16 [%0], {%1, %2, %3, %4};" :: "r"(addr), "r"(r0), "r"(r1), "r"(r2), "r"(r3) : "memory");
}
__device__ __forceinline__ uint32_t lds32(uint32_t a) { uint32_t v; asm volatile("ld.shared.u32 %0, [%1];" : "=r"(v) : "r"(a) : "memory"); return v; }
__device__ __forceinline__ uint2 lds64(uint32_t a) { uint2 v; asm volatile("ld.shared.v2.u32 {%0, %1}, [%2];" : "=r"(v.x), "=r"(v.y) : "r"(a) : "memory"); return v; }
__device__ __forceinline__ uint4 lds128(uint32_t a) { uint4 v; asm volatile("ld.shared.v4.u32 {%0, %1, %2, %3}, [%4];" : "=r"(v.x), "=r"(v.y), "=r"(v.z), "=r"(v.w) : "r"(a) : "memory"); return v; }
__device__ __forceinline__ void sts32(uint32_t a, uint32_t x) { asm volatile("st.shared.u32 [%0], %1;" :: "r"(a), "r"(x) : "memory"); }
__device__ __forceinline__ void sts128(uint32_t a, uint32_t x, uint32_t y, uint32_t z, uint32_t w) {
    asm volatile("st.shared.v4.u32 [%0], {%1, %2, %3, %4};" :: "r"(a), "r"(x), "r"(y), "r"(z), "r"(w) : "memory");
}
__device__ __forceinline__ float bflo(uint32_t v) { return __uint_as_float(v << 16); }
__device__ __forceinline__ float bfhi(uint32_t v) { return __uint_as_float(v & 0xffff0000u); }
__device__ __forceinline__ uint32_t hmul2bf(uint32_t a, uint32_t b) { uint32_t r; asm("mul.rn.bf16x2 %0, %1, %2;" : "=r"(r) : "r"(a), "r"(b)); return r; }
__device__ __forceinline__ uint32_t hadd2bf(uint32_t a, uint32_t b) { uint32_t r; asm("add.rn.bf16x2 %0, %1, %2;" : "=r"(r) : "r"(a), "r"(b)); return r; }
__device__ __forceinline__ uint32_t hsub2bf(uint32_t a, uint32_t b) { uint32_t r; asm("sub.rn.bf16x2 %0, %1, %2;" : "=r"(r) : "r"(a), "r"(b)); return r; }
__device__ __forceinline__ void mbar_init(uint32_t a, uint32_t c) { asm volatile("mbarrier.init.shared.b64 [%0], %1;" :: "r"(a), "r"(c)); }
__device__ __forceinline__ void mbar_wait(uint32_t a, uint32_t ph) {
    asm volatile("{\n.reg .pred p;\n.reg .u32 n;\nmov.u32 n, 0;\nWAIT_LOOP:\nmbarrier.try_wait.parity.shared.b64 p, [%0], %1;\n@p bra DONE;\nadd.u32 n, n, 1;\nsetp.lt.u32 p, n, 4000000;\n@p bra WAIT_LOOP;\nDONE:\n}" :: "r"(a), "r"(ph) : "memory");
}
__device__ __forceinline__ void mbar_wait_n(uint32_t a, uint32_t ph, uint32_t& n) {
    asm volatile("{\n.reg .pred p;\nWAIT_LOOP:\nmbarrier.try_wait.parity.shared.b64 p, [%1], %2;\n@p bra DONE;\nadd.u32 %0, %0, 1;\nsetp.lt.u32 p, %0, 4000000;\n@p bra WAIT_LOOP;\nDONE:\n}" : "+r"(n) : "r"(a), "r"(ph) : "memory");
}
__device__ __forceinline__ bool mbar_test(uint32_t a, uint32_t ph) {
    uint32_t r;
    asm volatile("{\n.reg .pred p;\nmbarrier.test_wait.parity.shared.b64 p, [%1], %2;\nselp.u32 %0, 1, 0, p;\n}" : "=r"(r) : "r"(a), "r"(ph) : "memory");
    return __all_sync(0xffffffffu, r != 0);
}
__device__ __forceinline__ void mbar_expect_tx(uint32_t a, uint32_t bytes) { asm volatile("mbarrier.arrive.expect_tx.shared.b64 _, [%0], %1;" :: "r"(a), "r"(bytes) : "memory"); }
__device__ __forceinline__ void mbar_arrive(uint32_t a) { asm volatile("mbarrier.arrive.shared.b64 _, [%0];" :: "r"(a) : "memory"); }
__device__ __forceinline__ void mbar_arrive2(uint32_t a) { asm volatile("mbarrier.arrive.shared.b64 _, [%0], 2;" :: "r"(a) : "memory"); }
__device__ __forceinline__ void tma_load_2d(uint32_t dst, const CUtensorMap* map, int c0, int c1, uint32_t bar) {
    asm volatile("cp.async.bulk.tensor.2d.shared::cluster.global.mbarrier::complete_tx::bytes [%0], [%1, {%3, %4}], [%2];"
        :: "r"(dst), "l"(map), "r"(bar), "r"(c0), "r"(c1) : "memory");
}
__device__ __forceinline__ void tma_load_5d(uint32_t dst, const CUtensorMap* map, int c0, int c4, uint32_t bar) {
    asm volatile("cp.async.bulk.tensor.5d.shared::cluster.global.mbarrier::complete_tx::bytes [%0], [%1, {%3, %5, %5, %5, %4}], [%2];"
        :: "r"(dst), "l"(map), "r"(bar), "r"(c0), "r"(c4), "r"(0) : "memory");
}
__device__ __forceinline__ void bulk_load(uint32_t dst, const void* src, uint32_t bytes, uint32_t bar) {
    asm volatile("cp.async.bulk.shared::cluster.global.mbarrier::complete_tx::bytes [%0], [%1], %2, [%3];" :: "r"(dst), "l"(src), "r"(bytes), "r"(bar) : "memory");
}
__device__ __forceinline__ void l2_prefetch(const void* p, uint32_t bytes) {
    asm volatile("cp.async.bulk.prefetch.L2.global [%0], %1;" :: "l"(p), "r"(bytes) : "memory");
}
__device__ __forceinline__ void wait_counter(const unsigned int* p, unsigned int target) {
    unsigned int cur; int spins = 0;
    #pragma unroll 1
    do {
        asm volatile("ld.relaxed.gpu.global.u32 %0, [%1];" : "=r"(cur) : "l"(p) : "memory");
        if ((int)(cur - target) >= 0) break;
        __nanosleep(20);
    } while (++spins < (1 << 22));
}
__device__ __forceinline__ void red_release(unsigned int* p) { asm volatile("red.release.gpu.global.add.u32 [%0], 1;" :: "l"(p) : "memory"); }
__device__ __forceinline__ uint32_t clk32() { uint32_t c; asm volatile("mov.u32 %0, %%clock;" : "=r"(c)); return c; }
__device__ __forceinline__ bool elect_one() {
    uint32_t r;
    asm volatile("{\n.reg .pred p;\nelect.sync _|p, 0xffffffff;\nselp.u32 %0, 1, 0, p;\n}" : "=r"(r));
    return r != 0;
}
#define PAUSE_NS 0
__device__ __forceinline__ void pause() { __nanosleep(PAUSE_NS); }
__device__ __forceinline__ int tid128() { int t; asm volatile("mov.u32 %0, %%tid.x;" : "=r"(t)); return t & 127; }
#define CTW(yr, yi, qx, qy) do { const float _r = (yr), _i = (yi); yr = _r * (qx) - _i * (qy); yi = _r * (qy) + _i * (qx); } while (0)
typedef __nv_bfloat162 bf2;
__device__ __forceinline__ bf2 asbf2(uint32_t v) { return *reinterpret_cast<bf2*>(&v); }
__device__ __forceinline__ uint32_t asu32(bf2 v) { return *reinterpret_cast<uint32_t*>(&v); }
template <int M> struct W16 { static constexpr uint32_t c = ct::bf16bits(ct::cos2048(128 * M)) * 0x10001u, s = ct::bf16bits(-ct::sin2048(128 * M)) * 0x10001u; };
__device__ __forceinline__ bf2 neg2(bf2 v) { return asbf2(asu32(v) ^ 0x80008000u); }
__device__ __forceinline__ void cmul2(bf2& r, bf2& i, bf2 wr, bf2 wi) {
    const bf2 a = r, b = i;
    r = __hfma2(a, wr, __hmul2(b, neg2(wi))); i = __hfma2(b, wr, __hmul2(a, wi));
}
__device__ __forceinline__ void bfly4(bf2* r, bf2* i, int o, int s) {
    const bf2 ar = __hadd2(r[o], r[o + 2 * s]), ai = __hadd2(i[o], i[o + 2 * s]), br = __hsub2(r[o], r[o + 2 * s]), bi = __hsub2(i[o], i[o + 2 * s]);
    const bf2 cr = __hadd2(r[o + s], r[o + 3 * s]), ci = __hadd2(i[o + s], i[o + 3 * s]), dr = __hsub2(r[o + s], r[o + 3 * s]), di = __hsub2(i[o + s], i[o + 3 * s]);
    r[o] = __hadd2(ar, cr); i[o] = __hadd2(ai, ci); r[o + 2 * s] = __hsub2(ar, cr); i[o + 2 * s] = __hsub2(ai, ci);
    r[o + s] = __hadd2(br, di); i[o + s] = __hsub2(bi, dr); r[o + 3 * s] = __hsub2(br, di); i[o + 3 * s] = __hadd2(bi, dr);
}
template <int M> __device__ __forceinline__ void tw16(bf2& r, bf2& i) {
    if (M == 4) { const bf2 a = r; r = i; i = neg2(a); }
    else cmul2(r, i, asbf2(W16<M>::c), asbf2(W16<M>::s));
}
__device__ __forceinline__ void tw16_all(bf2* r, bf2* i) {
    tw16<1>(r[5], i[5]); tw16<2>(r[6], i[6]); tw16<3>(r[7], i[7]); tw16<2>(r[9], i[9]); tw16<4>(r[10], i[10]); tw16<6>(r[11], i[11]);
    tw16<3>(r[13], i[13]); tw16<6>(r[14], i[14]); tw16<9>(r[15], i[15]);
}

#define DBAR 1
#define FBAR 2
#define SBAR 3
#define HBAR 6
#define WBAR 4
#define ZBAR 5
#define FULL(s) (bars + 8 * (s))
#define EMPTY(s) (bars + 8 * (RING + (s)))
#define XB (bars + 64)
#define X1B (bars + 72)
#define WQ(i) (bars + 144 + 8 * (i))
#define ZB (bars + 88)
#define EPB (bars + 96)
#define R0F (bars + 104)
#define HOK(i) (bars + 112 + 8 * (i))
#define EPO_OFF (BAR_OFF + 160)
#define SACT_OFF (BAR_OFF + 164)
#define LBAR 12
#define PSZ 8192
#define BND 2
#define PCW 100
#define WBUF(i) ((i) == 1 ? R1 : ((i) == 2 ? R1 + 16384 : R2 + 10240))
#define PC1 512
#define PC2 96
#define PCH 96
#define PCL 100
__device__ __forceinline__ void delay(int cycles) { if (cycles > 0) { const uint32_t c = clk32(); while ((int)(clk32() - c) < cycles) { } } }
__device__ __forceinline__ void pace(uint32_t& t, int cycles) { while ((int)(clk32() - t) < 0) { } t += cycles; }
__device__ __forceinline__ void pf_line(const void* p) { asm volatile("prefetch.global.L2 [%0];" :: "l"(p)); }

__device__ __forceinline__ float2 cis(int m) { return __ldg(reinterpret_cast<const float2*>(g_img.cs[m & 15][(m >> 4) & 127])); }
__device__ __forceinline__ void gen_dft(uint32_t dst, int j, int t, int b0, int b1, float scale, float c0) {
    const float c2 = 2.f * cis(t).x;
    float2 a = cis(t - 8 * b0 * t), b = cis(-8 * b0 * t);
    a.x *= scale; a.y *= scale; b.x *= scale; b.y *= scale;
    float2 z0 = b0 ? b : make_float2(c0, (j & 1) ? -c0 : c0);
    dst += j * 128;
    #pragma unroll 1
    for (int blk = b0; blk < b1; blk++) {
        float2 v[9];
        v[0] = b;
        v[1] = make_float2(fmaf(c2, b.x, -a.x), fmaf(c2, b.y, -a.y));
        #pragma unroll
        for (int k = 2; k < 9; k++) v[k] = make_float2(fmaf(c2, v[k - 1].x, -v[k - 2].x), fmaf(c2, v[k - 1].y, -v[k - 2].y));
        const uint32_t p = dst + (blk >> 2) * 16384, c = (2 * (blk & 3)) ^ (j & 7);
        sts128(p + c * 16, pack2(z0.x, v[1].x), pack2(v[2].x, v[3].x), pack2(v[4].x, v[5].x), pack2(v[6].x, v[7].x));
        sts128(p + (c ^ 1) * 16, pack2(z0.y, v[1].y), pack2(v[2].y, v[3].y), pack2(v[4].y, v[5].y), pack2(v[6].y, v[7].y));
        a = v[7]; b = v[8]; z0 = b;
    }
}

__device__ __forceinline__ void fft_p1(uint32_t sbase, int tile, int r, int db) {
    const uint32_t s16 = to16(sbase);
    float acc[64];
    wgmma_fence();
    ss128_z<1, 1>(acc, mkd(s16 + tile * 1024, R1, 16384, 1024, 1), mkd(s16, R0, 16384, 1024, 1));
    #pragma unroll
    for (int ks = 1; ks < 8; ks++) ss128<1, 1>(acc, mkd(s16 + tile * 1024, R1 + ks * 2048, 16384, 1024, 1), mkd(s16, R0 + ks * 2048, 16384, 1024, 1));
    wgmma_commit();
    const int tid = tid128();
    float g0 = 0.f;
    uint4* dst = g_X1 + (64 * tile + 2 * (tid >> 2)) * 2048 + (r >> 3) * 1024 + db * 128 + (r & 7) * 16 + (tid & 3);
    const bool spec = tile == 0 && tid < 4;
    const float2 w = cis(-64 * r);
    wgmma_wait<0>();
    reg_fence<64>(acc);
    uint32_t tp = clk32() + (threadIdx.x >> 5 & 7) * (PC1 / 8);
    #pragma unroll
    for (int c = 0; c < 4; c++) {
        const float* u = acc + 4 * (c >> 1) + (c & 1);
        #pragma unroll
        for (int ke = 0; ke < 2; ke++) {
            float v[8];
            #pragma unroll
            for (int z = 0; z < 8; z++) { const int ix = 8 * (z & 3) + 2 * (z >> 2); v[z] = ke ? u[ix] - u[ix + 32] : u[ix] + u[ix + 32]; }
            uint4 o = make_uint4(pack2(v[0], v[1]), pack2(v[2], v[3]), pack2(v[4], v[5]), pack2(v[6], v[7]));
            if (spec) {
                __stcg(dst + (128 + ke) * 2048 + 4 * c, make_uint4(pack2(v[4] * w.x, v[5] * w.x), pack2(v[6] * w.x, v[7] * w.x), pack2(v[4] * w.y, v[5] * w.y), pack2(v[6] * w.y, v[7] * w.y)));
                o.z = 0; o.w = 0;
            }
            pace(tp, PC1);
            __stcg(dst + ke * 2048 + 4 * c, o);
            const uint4 x = lds128(sbase + R0 + tile * 16384 + tid * 128 + (((2 * c + ke) ^ (tid & 7)) << 4)), gv = lds128(sbase + GATE_OFF + tile * 128 + (2 * c + ke) * 16);
            const uint32_t p0 = hmul2bf(x.x, gv.x), p1 = hmul2bf(x.y, gv.y), p2 = hmul2bf(x.z, gv.z), p3 = hmul2bf(x.w, gv.w);
            g0 += ((bflo(p0) + bfhi(p0)) + (bflo(p1) + bfhi(p1))) + ((bflo(p2) + bfhi(p2)) + (bflo(p3) + bfhi(p3)));
        }
    }
    __stcg(&g_gp[(16 * r + 2 * db + tile) * 128 + tid], g0);
}

__device__ __forceinline__ int w_first(int unit, int hb) { const int ka = unit >> 1, ke = unit & 1; return hb ? ((128 - ka) & 127) * 513 + 2 - ke : ka * 513 + ke; }
__device__ __forceinline__ void load_w(const CUtensorMap* wm, uint32_t sbase, int unit, int i) {
    const uint32_t bars = sbase + BAR_OFF;
    mbar_expect_tx(WQ(i >> 1), 16384);
    DBG_STAMP(108 + 2 * i);
    #pragma unroll 1
    for (int a = 0; a < 2; a++) {
        asm volatile("cp.async.bulk.tensor.3d.shared::cluster.global.mbarrier::complete_tx::bytes [%0], [%1, {%3, %4, %5}], [%2];"
            :: "r"(sbase + WBUF(i) + a * 8192), "l"(wm + (i & 1)), "r"(WQ(i >> 1)), "r"(w_first(unit, i >> 1) & ~7), "r"(0), "r"(8 * a) : "memory");
        delay(PCW);
    }
}
__device__ __forceinline__ uint32_t w_off(int e) { e &= 511; return (e >> 6) * 128 + ((((e >> 3) ^ (e >> 6)) & 7) << 4) + (e & 7) * 2; }
__device__ __forceinline__ void sts16(uint32_t a, uint32_t v) { asm volatile("st.shared.u16 [%0], %1;" :: "r"(a), "h"((unsigned short)v) : "memory"); }
__device__ __forceinline__ void load_paced(uint32_t dst, const uint8_t* src, int n, uint32_t bar) {
    #pragma unroll 1
    for (int i = 0; i < n; i++) { bulk_load(dst + i * PSZ, src + i * PSZ, PSZ, bar); delay(PCL); }
}
__device__ __forceinline__ void boundary() { while (clk32() == 0) { } asm volatile("" ::: "memory"); }
__device__ __forceinline__ void yield_to_scan(uint32_t sbase) {
    #pragma unroll 1
    for (int n = 0; n < 100000 && lds32(sbase + SACT_OFF); n++) __nanosleep(50);
}
template <int OFF> __device__ __forceinline__ uint32_t lds_w(uint32_t a, uint32_t b) {
    uint32_t l, h;
    asm volatile("ld.shared.u16 %0, [%2 + %4];\nld.shared.u16 %1, [%3 + %4];" : "=r"(l), "=r"(h) : "r"(a), "r"(b), "n"(OFF) : "memory");
    return __byte_perm(l, h, 0x5410);
}
template <int S> __device__ __forceinline__ void load_ws(uint32_t* w, uint32_t a, uint32_t b) {
    if constexpr (S < 16) { w[S] = lds_w<((S >> 2) + 4 * (S & 3)) * 1024>(a, b); load_ws<S + 1>(w, a, b); }
}
template <int TB> __device__ __forceinline__ void ss64(float* d, uint64_t a, uint64_t b) {
    asm volatile("wgmma.mma_async.sync.aligned.m64n64k16.f32.bf16.bf16 " L32 ", %32, %33, 1, 1, 1, 0, %34;\n" : R32(d) : "l"(a), "l"(b), "n"(TB));
}
template <int TB> __device__ __forceinline__ void ss64_z(float* d, uint64_t a, uint64_t b) {
    asm volatile("wgmma.mma_async.sync.aligned.m64n64k16.f32.bf16.bf16 " L32 ", %32, %33, 0, 1, 1, 0, %34;\n" : W32(d) : "l"(a), "l"(b), "n"(TB));
}

__device__ __forceinline__ void fft_p2(uint32_t sbase, uint32_t bars, int unit, const __nv_bfloat16* w_r, const __nv_bfloat16* w_i) {
    const uint32_t s16 = to16(sbase);
    const ct::Half* tb = &g_img.h[unit & 1];
    uint32_t P[16][4];
    {
        const int tid = tid128();
        uint32_t sp = 0, pt = 0;
        const uint4 t = __ldg(reinterpret_cast<const uint4*>(tb->tw[0][tid]));
        if (tid < 32 && !(unit & 1)) {
            const int k1 = ((tid & 16) ? (128 - (unit >> 1)) & 127 : unit >> 1) + 128 * (tid & 15), o1 = k1 * 513 + 32 * (tid & 16), o2 = ((2048 - k1) & 2047) * 513 + 32 * (tid & 16);
            sp = pack2(0.5f * (__bfloat162float(w_r[o1]) + __bfloat162float(w_r[o2])), 0.5f * (__bfloat162float(w_i[o1]) - __bfloat162float(w_i[o2])));
        }
        #pragma unroll
        for (int hb = 0; hb < 2; hb++) {
            const int e0 = w_first(unit, hb), z = (e0 & 1) + 2 * (tid & 3);
            if (z + 2 <= (e0 & 7)) pt |= (uint32_t)reinterpret_cast<const unsigned short*>(tid < 64 ? w_r : w_i)[((tid >> 2) & 15) * 65664 + (e0 & ~7) + 512 + z] << (16 * hb);
        }
        mbar_wait(X1B, 0);
        sts32(sbase + GATE_OFF + 4 * tid, pt);
        if (tid < 32) sts32(sbase + DSK_OFF + 4 * tid, sp);
        if (tid == 0) DBG_STAMP(17);
        #pragma unroll
        for (int h = 0; h < 2; h++) {
            float acc[64];
            if (h) boundary();
            wgmma_fence();
            ss128_z<1, 0>(acc, mkd(s16, R2, 1024, 128), mkd(s16, R1 + h * 16384, 2048, 128));
            #pragma unroll
            for (int s = 1; s < 4; s++) ss128<1, 0>(acc, mkd(s16, R2 + s * 2048, 1024, 128), mkd(s16, R1 + h * 16384 + s * 4096, 2048, 128));
            wgmma_commit();
            wgmma_wait<0>();
            reg_fence<64>(acc);
            bar_arrive_n(LBAR + h, 160);
            bf2 f[32];
            #pragma unroll
            for (int z = 0; z < 32; z++) { uint32_t u = pack2(acc[2 * z], acc[2 * z + 1]); asm volatile("" : "+r"(u) :: "memory"); f[z] = asbf2(u); }
            boundary();
            #pragma unroll
            for (int b = 0; b < 2; b++) {
                float d[32];
                if (b) boundary();
                #pragma unroll
                for (int z = 16 * b; z < 16 * b + 16; z++) { uint32_t u = asu32(f[z]); asm volatile("" : "+r"(u) :: "memory"); f[z] = asbf2(u); }
                #pragma unroll
                for (int z = 8 * b; z < 8 * b + 8; z++) cmul2(f[2 * z], f[2 * z + 1], asbf2((z & 1) ? t.z : t.x), asbf2((z & 1) ? t.w : t.y));
                wgmma_fence();
                #pragma unroll
                for (int pr = 0; pr < 2; pr++) {
                    const bf2* a = f + 16 * b + 8 * pr;
                    rs32_z(d + 16 * pr, asu32(a[0]), asu32(a[4]), asu32(a[2]), asu32(a[6]), mkd(s16, B16F_OFF, 128, 512));
                    rs32(d + 16 * pr, asu32(a[1]), asu32(a[5]), asu32(a[3]), asu32(a[7]), mkd(s16, B16F_OFF + 256, 128, 512));
                }
                wgmma_commit();
                wgmma_wait<0>();
                reg_fence<32>(d);
                #pragma unroll
                for (int rl = 0; rl < 4; rl++)
                    #pragma unroll
                    for (int i = 0; i < 4; i++) {
                        P[8 * h + 4 * b + rl][i] = pack2(d[16 * (rl >> 1) + 4 * i + 2 * (rl & 1)], d[16 * (rl >> 1) + 4 * i + 2 * (rl & 1) + 1]);
                        asm volatile("" : "+r"(P[8 * h + 4 * b + rl][i]) :: "memory");
                    }
            }
        }
    }
    if (tid128() == 0) DBG_STAMP(18);
    #pragma unroll 1
    for (int hb = 0; hb < 2; hb++) {
        const int tid = tid128(), sh = w_first(unit, hb) & 7;
        const uint32_t br = sbase + (hb ? WBUF(2) : WBUF(0)), bi = sbase + (hb ? WBUF(3) : WBUF(1));
        const uint32_t pt = lds32(sbase + GATE_OFF + 4 * tid) >> (16 * hb), sp = lds32(sbase + DSK_OFF + 4 * (tid & 31));
        if (tid == 0) DBG_STAMP(100 + 4 * hb);
        mbar_wait(WQ(hb), 0);
        if (tid == 0) DBG_STAMP(101 + 4 * hb);
        if ((sh & 1) + 2 * (tid & 3) + 2 <= sh) sts16((tid < 64 ? br : bi) + ((tid >> 2) & 15) * 1024 + ((sh & 1) + 2 * (tid & 3)) * 2, pt);
        bar_sync_n(FBAR, 128);
        if (!(unit & 1) && (tid >> 4) == hb) {
            const uint32_t a = w_off(sh + 510 * hb) + (tid & 15) * 1024;
            sts16(br + a, sp); sts16(bi + a, sp >> 16);
        }
        __syncwarp();
        const int pos = 128 * (tid & 3) + 2 * (tid >> 2);
        const bool rot = hb && unit >= 2;
        const uint32_t o0 = w_off(sh + (hb ? 510 - pos : pos)) - (rot ? 1024 : 0), o1 = w_off(sh + (hb ? 446 - pos : pos + 64)) - (rot ? 1024 : 0), oz = rot ? 16384 : 0;
        uint32_t wr[16], wi[16];
        wr[0] = lds_w<0>(br + o0 + oz, br + o1 + oz); wi[0] = lds_w<0>(bi + o0 + oz, bi + o1 + oz);
        load_ws<1>(wr, br + o0, br + o1); load_ws<1>(wi, bi + o0, bi + o1);
        bf2 vr[16], vi[16];
        #pragma unroll
        for (int r = 0; r < 16; r++) { vr[r] = asbf2(P[r][0]); vi[r] = asbf2(P[r][2]); P[r][0] = P[r][1]; P[r][2] = P[r][3]; }
        #pragma unroll
        for (int r0 = 0; r0 < 4; r0++) bfly4(vr, vi, r0, 4);
        tw16_all(vr, vi);
        #pragma unroll
        for (int k1 = 0; k1 < 4; k1++) bfly4(vr, vi, 4 * k1, 1);
        #pragma unroll
        for (int s = 0; s < 16; s++) cmul2(vr[s], vi[s], asbf2(wr[s]), asbf2(wi[s]));
        if (tid == 0) DBG_STAMP(103 + 4 * hb);
        if (hb == 0) bar_arrive_n(LBAR + 2, 160); else bar_sync_n(FBAR, 128);
        boundary();
        #pragma unroll
        for (int k1 = 0; k1 < 4; k1++) bfly4(vi, vr, 4 * k1, 1);
        tw16_all(vi, vr);
        #pragma unroll
        for (int r0 = 0; r0 < 4; r0++) bfly4(vi, vr, r0, 4);
        #pragma unroll
        for (int r = 0; r < 16; r++) { P[r][1] = asu32(vr[r]); P[r][3] = asu32(vi[r]); }
    }
    if (tid128() == 0) DBG_STAMP(19);
    {
        const int tid = tid128();
        const uint4 t = __ldg(reinterpret_cast<const uint4*>(tb->tw[1][tid]));
        const uint32_t zero = unit >> 8;
        const uint32_t sa = sbase + R1 + ((tid >> 3) & 1) * 1024 + (2 * (tid >> 5) + ((tid >> 4) & 1)) * 128 + (tid & 7) * 16;
        float acc[2][16];
        #pragma unroll
        for (int pr = 0; pr < 9; pr++) {
            if (BND && (pr % BND) == 0) boundary();
            if (pr < 8) {
                uint32_t a[8];
                #pragma unroll
                for (int z = 0; z < 8; z++) asm volatile("xor.b32 %0, %1, %2;" : "=r"(a[z]) : "r"(P[2 * pr + (z >> 2)][z & 3]), "r"(zero) : "memory");
                wgmma_fence();
                rs32_z(acc[pr & 1], a[0], a[4], a[1], a[5], mkd(s16, R2 + 8192, 128, 512));
                rs32(acc[pr & 1], a[2], a[6], a[3], a[7], mkd(s16, R2 + 8192 + 256, 128, 512));
                wgmma_commit();
            }
            if (pr > 0) {
                if (pr < 8) wgmma_wait<1>(); else wgmma_wait<0>();
                reg_fence<16>(acc[(pr - 1) & 1]);
                #pragma unroll
                for (int rl = 0; rl < 2; rl++) {
                    const float* a = acc[(pr - 1) & 1] + 2 * rl;
                    bf2 r0 = asbf2(pack2(a[0], a[1])), r1 = asbf2(pack2(a[4], a[5])), i0 = asbf2(pack2(a[8], a[9])), i1 = asbf2(pack2(a[12], a[13]));
                    cmul2(r0, i0, asbf2(t.x), asbf2(t.y)); cmul2(r1, i1, asbf2(t.z), asbf2(t.w));
                    stsm_x4(sa + (2 * pr - 2 + rl) * 2048, asu32(r0), asu32(r1), asu32(i0), asu32(i1));
                }
            }
        }
    }
    fence_async();
    bar_sync_n(FBAR, 128);
    if (tid128() == 0) DBG_STAMP(20);
    {
        const int tid = tid128(), ka = unit >> 1;
        uint8_t* dst = reinterpret_cast<uint8_t*>(g_X2) + (2 * (tid >> 5)) * X2_IMG + (unit & 1) * (X2_IMG / 2)
                     + (16 * (ka >> 3) + 8 * ((tid >> 4) & 1) + (ka & 7)) * 128 + ((((tid >> 1) & 7) ^ (ka & 7)) << 4) + (tid & 1) * 8;
        float acc[32];
        uint32_t o[16], tp = 0;
        #pragma unroll 1
        for (int h = 0; h < 4; h++) {
            const uint32_t b16 = s16 + (h & 3) * 512;
            wgmma_fence();
            ss64_z<1>(acc, mkd(s16, R2, 128, 1024), mkd(b16, R1, 128, 1024));
            #pragma unroll
            for (int s = 1; s < 4; s++) ss64<1>(acc, mkd(s16, R2 + s * 256, 128, 1024), mkd(b16, R1 + s * 256, 128, 1024));
            wgmma_commit();
            if (h > 0) {
                yield_to_scan(sbase);
                if ((int)(clk32() - tp) > PC2) tp = clk32();
                #pragma unroll
                for (int z = 0; z < 8; z++) { pace(tp, PC2); __stcg(reinterpret_cast<uint2*>(dst + (8 * (z >> 1) + (z & 1)) * X2_IMG), make_uint2(o[2 * z], o[2 * z + 1])); }
                dst += 32 * X2_IMG;
            } else tp = clk32();
            wgmma_wait<0>();
            reg_fence<32>(acc);
            #pragma unroll
            for (int z = 0; z < 8; z++) { const float* a = acc + 8 * (z >> 1) + 2 * (z & 1); o[2 * z] = pack2(a[0], a[1]); o[2 * z + 1] = pack2(a[4], a[5]); }
        }
        #pragma unroll
        for (int z = 0; z < 8; z++) { pace(tp, PC2); __stcg(reinterpret_cast<uint2*>(dst + (8 * (z >> 1) + (z & 1)) * X2_IMG), make_uint2(o[2 * z], o[2 * z + 1])); }
    }
}

struct Maps { CUtensorMap Bre, Bim, X, Xr, Cre, Cim, W[2]; };
#define PSL 100
#define MAPV 0
#define SP1 0
#define SP2 2
#define GBAR 10
#define KBAR 11
#define HOLD 15
#define EAGG 8
#define YP1 1
#define PCR 96
#define PCG 0
#define YIELD 1u
#define PD0 20
#define PFC 12000
#define PFCS 2000
#define PFX 4
#define PFW 5000
#define PFB 9000

#define SBASE 0x400u
template <int TA> __device__ __forceinline__ void mma_round(float* acc, uint32_t a16, uint32_t ph, bool lead, int accum, int it, uint32_t& nw) {
    constexpr uint32_t bars = SBASE + BAR_OFF;
    #pragma unroll
    for (int s = 0; s < RING; s++) {
        mbar_wait_n(FULL(s), ph, nw);
        wgmma_fence();
        #pragma unroll
        for (int k = 0; k < 4; k++) {
            const uint64_t da = TA ? mkd(a16, s * STGB + k * 256, 128, 1024) : mkd(a16, s * STGB + k * 32, 16, 1024, 1);
            const uint64_t db = mkd(SBASE / 16, s * STGB + 16384 + k * 32, 16, 1024, 1);
            if (k == 0 && s == 0) ss128_p<TA, 0>(acc, da, db, accum); else ss128<TA, 0>(acc, da, db);
        }
        wgmma_commit();
        wgmma_wait<1>();
        if (threadIdx.x == 0) DBG_STAMP(32 + it + s);
        if (lead && (s > 0 || accum)) mbar_arrive(EMPTY((s + RING - 1) % RING));
    }
}
__device__ __forceinline__ void gemm_main(float* A, int wg, int warp, int lane) {
    constexpr uint32_t bars = SBASE + BAR_OFF;
    const bool lead = tid128() == 0;
    const uint32_t a16 = SBASE / 16 + wg * 512;
    uint32_t nw = 0;
    #pragma unroll 1
    for (int half = 0; half < 2; half++) {
        #pragma unroll 1
        for (int rd = 0; rd < 4; rd++) mma_round<0>(A, a16, rd & 1, lead, rd, 16 * half + 4 * rd, nw);
        mbar_wait_n(R0F, half, nw);
        const uint32_t a = SBASE + R0 + wg * 16384 + (lane & 3) * 2048 + (((16 * warp + (lane >> 2)) ^ (2 * (lane & 3))) << 4);
        wgmma_wait<0>();
        reg_fence<64>(A);
        if (lead) mbar_arrive(EMPTY(RING - 1));
        #pragma unroll
        for (int c = 0; c < 8; c++) {
            const float* u = A + c;
            sts128(a + (c >> 2) * 8192 + (c & 1) * 1024 + ((c >> 1) & 1) * 128, pack2(u[0], u[8]), pack2(u[16], u[24]), pack2(u[32], u[40]), pack2(u[48], u[56]));
        }
        bar_arrive_n(DBAR, 384);
        if (threadIdx.x == 0) DBG_STAMP(1 + half);
        if (HOLD >= 0) bar_sync_n(KBAR, 384);
    }
    #pragma unroll 1
    for (int rd = 0; rd < 8; rd++) mma_round<1>(A, a16, rd & 1, lead, rd, 32 + 4 * rd, nw);
}

__global__ void __launch_bounds__(640, 1)
fused_kernel(const __grid_constant__ Maps mp, const __nv_bfloat16* __restrict__ x,
             const __nv_bfloat16* __restrict__ w_r, const __nv_bfloat16* __restrict__ w_i,
             const __nv_bfloat16* __restrict__ lam_re, const __nv_bfloat16* __restrict__ lam_im,
             const __nv_bfloat16* __restrict__ log_dt, const __nv_bfloat16* __restrict__ dskip,
             const __nv_bfloat16* __restrict__ gate_w,
             const __nv_bfloat16* __restrict__ Cre, const __nv_bfloat16* __restrict__ Cim,
             const __nv_bfloat16* __restrict__ Bre, const __nv_bfloat16* __restrict__ Bim, float* __restrict__ out, unsigned int full) {
    extern __shared__ __align__(1024) uint8_t smem[];
    if (smem_u32(smem) != SBASE) __trap();
    constexpr uint32_t sbase = SBASE;
    constexpr uint32_t bars = sbase + BAR_OFF;
    const int tid = threadIdx.x, lane = tid & 31;
    const int wg = __shfl_sync(0xffffffffu, tid >> 7, 0), warp = __shfl_sync(0xffffffffu, (tid >> 5) & 3, 0);
    int cta = blockIdx.x;
    {
        unsigned int smid, nsm;
        asm volatile("mov.u32 %0, %%smid;" : "=r"(smid));
        asm volatile("mov.u32 %0, %%nsmid;" : "=r"(nsm));
        if (nsm == full) {
            const int t = smid >> 1, u = (t - 32) / 7;
            const int g = t < 32 ? (t & 7) : (t < 60 ? t - 31 - 7 * u : 0), idx = t < 32 ? (t >> 3) : (t < 60 ? 4 + u : t - 58);
            const int lg = (0x73216540 >> (4 * g)) & 7;
            cta = ((t & ~1) == 60 ? 8 + 2 * t : 16 * lg + 2 * idx) + (smid & 1);
        }
    }
    const int cb = 4 * (cta >> 6) + (cta & 3), tc = (cta >> 2) & 15;
    const int db = 4 * ((cta >> 4) & 1) + (cta & 3), rc = 4 * ((cta >> 5) & 3) + ((cta >> 2) & 3);
    const long long t_start = clock64();
    if (tid >= 512 && tid < 544 && elect_one()) {
        DBG_STAMP(0); DBG_RAW(98, (cta + 1) * 1000);
        for (int s = 0; s < RING; s++) { mbar_init(FULL(s), 1); mbar_init(EMPTY(s), 2); }
        for (int i = 0; i < 12; i++) mbar_init(XB + 8 * i, i >= 10 ? 2 : 1);
        sts32(sbase + SACT_OFF, 0u); sts32(sbase + SACT_OFF + 8, 0u);
        asm volatile("fence.mbarrier_init.release.cluster;" ::: "memory");
        fence_async();
        if (cta < 128) {
            #pragma unroll
            for (int s = 0; s < RING; s++) {
                mbar_expect_tx(FULL(s), STGB);
                tma_load_2d(sbase + s * STGB, &mp.Bre, s * 64, cb * 128, FULL(s));
                tma_load_2d(sbase + s * STGB + 8192, &mp.Bim, s * 64, cb * 128, FULL(s));
                tma_load_2d(sbase + s * STGB + 16384, &mp.X, s * 64, tc * 128, FULL(s));
            }
        }
    }
    __syncthreads();
    if (wg == 4) {
        asm volatile("setmaxnreg.dec.sync.aligned.u32 24;");
        if (warp == 0) {
            if (cta < 128 && elect_one()) {
                uint32_t nw = 0;
                #pragma unroll 1
                for (int rd = 1; rd < 8; rd++) {
                    const int row = cb * 128 + (rd >> 2) * 64, kc = (rd & 3) * 256;
                    #pragma unroll
                    for (int s = 0; s < RING; s++) {
                        mbar_wait_n(EMPTY(s), (rd - 1) & 1, nw);
                        mbar_expect_tx(FULL(s), STGB);
                        tma_load_2d(sbase + s * STGB, &mp.Bre, kc + s * 64, row, FULL(s));
                        tma_load_2d(sbase + s * STGB + 8192, &mp.Bim, kc + s * 64, row, FULL(s));
                        tma_load_2d(sbase + s * STGB + 16384, &mp.X, kc + s * 64, tc * 128, FULL(s));
                    }
                }
                const uint8_t* hs = reinterpret_cast<const uint8_t*>(g_h) + rc * 32 * 16384;
                #pragma unroll 1
                for (int rd = 8; rd < 16; rd++) {
                    const CUtensorMap* cm = (rd & 2) ? &mp.Cim : &mp.Cre;
                    const int kc = (rd & 1) * 512 + (rd & 4) * 16;
                    #pragma unroll
                    for (int s = 0; s < RING; s++) {
                        mbar_wait_n(EMPTY(s), (rd - 1) & 1, nw);
                        mbar_expect_tx(FULL(s), STGB);
                        tma_load_5d(sbase + s * STGB + 16384, cm, kc + s * 128, db * 4, FULL(s));
                        tma_load_5d(sbase + s * STGB + 24576, cm, kc + s * 128, db * 4 + 32, FULL(s));
                        if (s == 0) { mbar_wait_n(HOK((rd >> 1) & 3), 0, nw); if (!(rd & 3)) DBG_STAMP(13 + ((rd >> 2) & 1)); }
                        bulk_load(sbase + s * STGB, hs + s * 16384, 16384, FULL(s));
                    }
                    hs += 4 * 16384;
                }
            }
        } else if (warp == 1) {
            if (cta < 130) {
                if (cta < 128) bar_sync_n(GBAR, 288);
                mbar_wait(EPB, 0);
                const unsigned int epoch = lds32(sbase + EPO_OFF);
                const bool one = elect_one();
                if (one) {
                    if (cta < 128) { mbar_arrive(R0F); red_release(&g_cnt1); DBG_STAMP(15); }
                    mbar_expect_tx(X1B, ((ABL & 8) ? PSZ : 32768) + 2048 + 10240);
                    bulk_load(sbase + B16F_OFF, g_img.b16f, 2048, X1B);
                    bulk_load(sbase + R2, g_img.h[cta & 1].m4, 10240, X1B);
                    wait_counter(&g_cnt1, 128u * epoch);
                    DBG_STAMP(8);
                    load_paced(sbase + R1, reinterpret_cast<const uint8_t*>((ABL & 8) ? reinterpret_cast<const uint4*>(x) : g_X1 + cta * 2048), (ABL & 8) ? 1 : 32768 / PSZ, X1B);
                }
                #pragma unroll 1
                for (int i = 0; i < 4; i++) {
                    if (one) load_w(mp.W, sbase, cta, i);
                    __syncwarp();
                    bar_sync_n(LBAR + i, 160);
                }
                if (one) {
                    red_release(&g_cnt2);
                    DBG_STAMP(30);
                    if (cta < 128) {
                        const uint8_t* img = reinterpret_cast<const uint8_t*>(g_X2) + (8 * rc + db) * X2_IMG;
                        mbar_expect_tx(ZB, 32768);
                        wait_counter(&g_cnt2, 130u * epoch);
                        DBG_STAMP(31);
                        load_paced(sbase + R1, img, 16384 / PSZ, ZB);
                        load_paced(sbase + R1 + 16384, img + X2_IMG / 2, 16384 / PSZ, ZB);
                    }
                }
            }
        } else if (warp == 2) {
            if (cta < 128) {
                const uint8_t* xp = reinterpret_cast<const uint8_t*>(x) + (cta * 16 + (lane & 15)) * 2048 + (lane >> 4) * 128;
                const uint8_t* bp = reinterpret_cast<const uint8_t*>((lane & 16) ? Bim : Bre) + (cb * 128 + tc * 4 + ((lane >> 2) & 3)) * 2048 + (lane & 3) * 128;
                #pragma unroll 1
                for (int k = 4; k < 16; k++) {
                    if (k == PFX && lane == 0) {
                        mbar_expect_tx(XB, 32768);
                        #pragma unroll 1
                        for (int i = 0; i < 8; i++) tma_load_2d(sbase + R0 + i * 4096, &mp.Xr, rc * 1024 + db * 64 + (i >> 2) * 512, (i & 3) * 32, XB);
                    }
                    __syncwarp();
                    if ((k & 3) == 0) pf_line(bp + k * 128);
                    if (!(k & 1)) pf_line(xp + k * 128);
                }
                if ((cta & 63) < 8) pf_line(reinterpret_cast<const uint8_t*>(&g_img) + (cta & 63) * 4096 + lane * 128);
                while (clock64() - t_start < PFW) { }
                const uint32_t wrow = (((cta & 1) ? 128 - (cta >> 1) : (cta >> 1)) + 128 * (lane >> 1)) & 2047;
                const uint8_t* wp = reinterpret_cast<const uint8_t*>(lane & 1 ? w_i : w_r) + wrow * 1026u;

                #pragma unroll 1
                for (int k = 0; k < ((ABL & 4) ? 0 : 9); k++) { pf_line(wp + (k < 8 ? k * 128 : 1024)); __nanosleep(200); }
                while (clock64() - t_start < PFB) { }
                #pragma unroll 1
                for (int k = 0; k < 16; k += 4) { pf_line(bp + 64 * 2048 + k * 128); __nanosleep(200); }
                const uint8_t* cp = reinterpret_cast<const uint8_t*>((lane & 16) ? Cim : Cre) + (cta * 8 + (lane & 7)) * 2048 + (lane & 8) * 32;
                #pragma unroll 1
                for (int k = 0; k < 8; k++) {
                    while (clock64() - t_start < PFC + k * PFCS) { __nanosleep(100); }
                    pf_line(cp + (k & 3) * 512 + (k >> 2) * 128);
                }
            }
        } else {
            unsigned int epoch = 0;
            if (lane == 0) {
                epoch = atomicAdd(&g_ticket, 1u);
                epoch = (full ? epoch / NCTA : epoch / 130u) + 1u;
                sts32(sbase + EPO_OFF, epoch);
                mbar_arrive(EPB);
            }
            __syncwarp();
            if (cta < 128) {
                #pragma unroll 1
                for (int i = 0; i < 4; i++) {
                    bar_sync_n(HBAR + i, 160);
                    if (lane == 0) {
                        red_release(&g_cnth(i));
                        if (!(i & 1)) DBG_STAMP(4 + (i >> 1));
                        wait_counter(&g_cnth(i), 128u * epoch);
                        mbar_arrive(HOK(i));
                    }
                    __syncwarp();
                }
                if (lane == 0) {
                    mbar_expect_tx(XB, 32768);
                    #pragma unroll 1
                    for (int i = 0; i < 8; i++) { tma_load_2d(sbase + R0 + i * 4096, &mp.Xr, rc * 1024 + db * 64 + (i >> 2) * 512, (i & 3) * 32, XB); __nanosleep(150); }
                }
            } else if (cta >= 130 && lane == 0) {
                #pragma unroll 1
                for (int i = 0; i < (1 << 22); i++) {
                    __nanosleep(200);
                    if ((int)(*reinterpret_cast<volatile unsigned int*>(&g_ticket) - NCTA * epoch) >= 0) break;
                }
            }
        }
    } else if (wg >= 2) {
      if (cta < 128) {
          gen_dft(sbase + R1, tid128(), 16 * tid128() + rc, 4 * wg - 8, 4 * wg - 4, 1.f, 0.5f);
          if (tid128() < 8) { const uint4 gl = __ldg(reinterpret_cast<const uint4*>(gate_w) + db * 8 + (wg - 2) * 64 + lane); sts128(sbase + GATE_OFF + (wg - 2) * 128 + lane * 16, gl.x, gl.y, gl.z, gl.w); }
          fence_async();
          bar_sync_n(wg, 128);
          mbar_wait(XB, 0);
          if (tid == 256) DBG_STAMP(9);
          fft_p1(sbase, wg - 2, rc, db);
          bar_arrive_n(GBAR, 288);
      }
      if (wg == 3) {
        asm volatile("setmaxnreg.inc.sync.aligned.u32 128;");
        if (cta < 128) {
            const int t128 = tid & 127;
            const int pq = cb * 128 + (t128 & 1) * 64 + (t128 >> 1);
            const uint32_t prm = (uint32_t)__ldg(reinterpret_cast<const unsigned short*>(lam_re) + pq) | ((uint32_t)__ldg(reinterpret_cast<const unsigned short*>(lam_im) + pq) << 16);
            const float pdt = __bfloat162float(log_dt[pq]);
            if (cta < 128) {
                mbar_wait(EPB, 0);
                #pragma unroll 1
                for (int half = 0; half < 2; half++) {
                    const int t1 = tid128(), ch = t1 >> 1, hf = t1 & 1, p = cb * 128 + half * 64 + ch;
                    const float dt = bf16r(expf(__shfl_sync(0xffffffffu, pdt, (lane & 30) + half)));
                    const uint32_t pl = __shfl_sync(0xffffffffu, prm, (lane & 30) + half);
                    const float lr = bflo(pl), li = bfhi(pl);
                    float2 lam;
                    {
                        const float er = expf(dt * lr);
                        float sn, cs; sincospif(dt * li * 0.31830988618379067154f, &sn, &cs);
                        lam = make_float2(er * cs, er * sn);
                    }
                    const float den = lr * lr + li * li;
                    float cr = __fdividef((lam.x - 1.f) * lr + lam.y * li, den), ci = __fdividef(lam.y * lr - (lam.x - 1.f) * li, den);
                    float2 l16 = cmul(lam, lam); l16 = cmul(l16, l16); l16 = cmul(l16, l16); l16 = cmul(l16, l16);
                    float2 l64 = cmul(l16, l16); l64 = cmul(l64, l64);
                    const unsigned int par = lds32(sbase + EPO_OFF) & 1u;
                    {
                        uint32_t z = __float_as_uint(cr) ^ __float_as_uint(ci) ^ __float_as_uint(l64.x) ^ __float_as_uint(l64.y);
                        if (z == 0x9e3779b9u) sts32(sbase + SACT_OFF + 4, z);
                    }
                    bar_sync_n(DBAR, 384);
                    if (t1 == 0) DBG_STAMP(21 + 4 * half);
                    uint2 ur[16], ui[16];
                    #pragma unroll
                    for (int r = 0; r < 16; r++) {
                        const uint32_t a = sbase + R0 + r * 1024 + ((ch ^ (r & 6)) << 4) + hf * 8;
                        ur[r] = lds64(a); ui[r] = lds64(a + 16384);
                    }
                    if (HOLD >= 0) { if (cta > 999) sts32(sbase + SACT_OFF + 4, ui[HOLD].y); bar_arrive_n(KBAR, 384); boundary(); }
                    float2 e[4];
                    e[0] = make_float2(bflo(ur[0].x), bflo(ui[0].x)); e[1] = make_float2(bfhi(ur[0].x), bfhi(ui[0].x));
                    e[2] = make_float2(bflo(ur[0].y), bflo(ui[0].y)); e[3] = make_float2(bfhi(ur[0].y), bfhi(ui[0].y));
                    #pragma unroll
                    for (int r = 1; r < 16; r++) {
                        e[0] = cfma(lam, e[0], make_float2(bflo(ur[r].x), bflo(ui[r].x))); e[1] = cfma(lam, e[1], make_float2(bfhi(ur[r].x), bfhi(ui[r].x)));
                        e[2] = cfma(lam, e[2], make_float2(bflo(ur[r].y), bflo(ui[r].y))); e[3] = cfma(lam, e[3], make_float2(bfhi(ur[r].y), bfhi(ui[r].y)));
                        ur[r] = make_uint2(pack2(e[0].x, e[1].x), pack2(e[2].x, e[3].x)); ui[r] = make_uint2(pack2(e[0].y, e[1].y), pack2(e[2].y, e[3].y));
                        if (SP1 && (r % (SP1 ? SP1 : 1)) == 0) { asm volatile("" : "+r"(ur[r].x), "+r"(ur[r].y), "+r"(ui[r].x), "+r"(ui[r].y) :: "memory"); lam.x = __shfl_sync(0xffffffffu, lam.x, lane); }
                    }
                    e[1] = cfma(l16, e[0], e[1]); e[2] = cfma(l16, e[1], e[2]); e[3] = cfma(l16, e[2], e[3]);
                    float2 E0;
                    E0.x = __shfl_xor_sync(0xffffffffu, e[3].x, 1); E0.y = __shfl_xor_sync(0xffffffffu, e[3].y, 1);
                    if (hf && tc < 15) {
                        const float2 ag = cfma(l64, E0, e[3]);
                        const unsigned long long w = (unsigned long long)((__float_as_uint(ag.x) & ~1u) | par) | ((unsigned long long)((__float_as_uint(ag.y) & ~1u) | par) << 32);
                        asm volatile("st.relaxed.gpu.global.u64 [%0], %1;" :: "l"(&g_agg[tc * P_DIM + p]), "l"(w) : "memory");
                    }
                    const uint2* src = reinterpret_cast<const uint2*>(g_agg) + (tc - 1 - hf) * P_DIM + p;
                    const int nv = tc - hf;
                    uint2 v[8];
                    #pragma unroll
                    for (int i = 0; i < 8; i++) {
                        v[i] = make_uint2(par, par);
                        if (2 * i < nv) asm volatile("ld.relaxed.gpu.global.v2.u32 {%0, %1}, [%2];" : "=r"(v[i].x), "=r"(v[i].y) : "l"(src - i * 2 * P_DIM) : "memory");
                    }
                    bar_sync_n(SBAR, 128);
                    if (t1 == 0) { mbar_arrive(R0F); DBG_STAMP(22 + 4 * half); }
                    {
                        cr += __uint_as_float(lds32(sbase + SACT_OFF + 8));
                        ci += __uint_as_float(lds32(sbase + SACT_OFF + 8));
                        const bf2 c2 = asbf2(pack2(cr, cr)), n2 = asbf2(pack2(-cr, -cr)), s2 = asbf2(pack2(-ci, -ci));
                        #pragma unroll
                        for (int r = 0; r < 16; r++) {
                            const bf2 a = asbf2(ur[r].x), b = asbf2(ui[r].x), c = asbf2(ur[r].y), d = asbf2(ui[r].y);
                            ur[r].x = asu32(__hfma2(c2, a, __hmul2(s2, b))); ui[r].x = asu32(__hfma2(n2, b, __hmul2(s2, a)));
                            ur[r].y = asu32(__hfma2(c2, c, __hmul2(s2, d))); ui[r].y = asu32(__hfma2(n2, d, __hmul2(s2, c)));
                        }
                    }
                    const float2 l32 = cmul(l16, l16), l128 = cmul(l64, l64), l256 = cmul(l128, l128);
                    #pragma unroll 1
                    for (int spins = 0; spins < (1 << 20); spins++) {
                        uint32_t bad = 0;
                        #pragma unroll
                        for (int i = 0; i < 8; i++) bad |= (v[i].x ^ par) | (v[i].y ^ par);
                        if (!__any_sync(0xffffffffu, bad & 1u)) break;
                        #pragma unroll
                        for (int i = 0; i < 8; i++)
                            if (2 * i < nv) asm volatile("ld.relaxed.gpu.global.v2.u32 {%0, %1}, [%2];" : "+r"(v[i].x), "+r"(v[i].y) : "l"(src - i * 2 * P_DIM) : "memory");
                    }
                    if (t1 == 0) { sts32(sbase + SACT_OFF, YIELD); DBG_STAMP(23 + 4 * half); }
                    float2 H = make_float2(__uint_as_float(v[7].x), __uint_as_float(v[7].y));
                    #pragma unroll
                    for (int i = 6; i >= 0; i--) H = cfma(l256, H, make_float2(__uint_as_float(v[i].x), __uint_as_float(v[i].y)));
                    if (hf) H = cmul(H, l128);
                    H.x += __shfl_xor_sync(0xffffffffu, H.x, 1); H.y += __shfl_xor_sync(0xffffffffu, H.y, 1);
                    float2 st[4];
                    st[0] = hf ? cfma(l64, H, E0) : H;
                    st[1] = cfma(l16, st[0], e[0]); st[2] = cfma(l32, st[0], e[1]); st[3] = cfma(l16, cmul(l32, st[0]), e[2]);
                    const bf2 gr0 = asbf2(pack2(cr * st[0].x - ci * st[0].y, cr * st[1].x - ci * st[1].y)), gr1 = asbf2(pack2(cr * st[2].x - ci * st[2].y, cr * st[3].x - ci * st[3].y));
                    const bf2 gi0 = asbf2(pack2(-ci * st[0].x - cr * st[0].y, -ci * st[1].x - cr * st[1].y)), gi1 = asbf2(pack2(-ci * st[2].x - cr * st[2].y, -ci * st[3].x - cr * st[3].y));
                    uint2* dst = reinterpret_cast<uint2*>(g_h + (half * 16 + cb) * 1024 + tc * 64) + t1;
                    lam.y = -lam.y;
                    float2 z = lam;
                    uint32_t pw[16], tp = clk32() + warp * (PCH / 4);
                    #pragma unroll
                    for (int r = 0; r < 16; r++) {
                        pw[r] = pack2(z.x, z.y); z = cmul(z, lam);
                        const bf2 pr = __low2bfloat162(asbf2(pw[r])), pi = __high2bfloat162(asbf2(pw[r]));
                        pace(tp, PCR);
                        __stcg(dst + r * 65536, make_uint2(asu32(__hfma2(pr, gr0, __hfma2(pi, neg2(gi0), asbf2(ur[r].x)))), asu32(__hfma2(pr, gr1, __hfma2(pi, neg2(gi1), asbf2(ur[r].y))))));
                    }
                    bar_arrive_n(HBAR + 2 * half, 160);
                    if (t1 == 0) DBG_STAMP(24 + 4 * half);
                    tp += PCG;
                    #pragma unroll
                    for (int r = 0; r < 16; r++) {
                        const bf2 pr = __low2bfloat162(asbf2(pw[r])), pi = __high2bfloat162(asbf2(pw[r]));
                        pace(tp, PCH);
                        __stcg(dst + r * 65536 + 16384, make_uint2(asu32(__hfma2(pr, gi0, __hfma2(pi, gr0, asbf2(ui[r].x)))), asu32(__hfma2(pr, gi1, __hfma2(pi, gr1, asbf2(ui[r].y))))));
                    }
                    bar_arrive_n(HBAR + 2 * half + 1, 160);
                    if (t1 == 0) sts32(sbase + SACT_OFF, 0u);
                }
            }
        }
      } else {
        asm volatile("setmaxnreg.inc.sync.aligned.u32 136;");
        if (cta < 130) {
            if (tid128() == 0) DBG_STAMP(16);
            fft_p2(sbase, bars, cta, w_r, w_i);
            bar_sync_n(LBAR + 3, 160);
            if (tid128() == 0) DBG_STAMP(29);
            if (cta < 128) {
                const int j = tid128();
                if (j < 16) {
                    const uint2 d0 = __ldg(reinterpret_cast<const uint2*>(dskip) + db * 16 + j), d1 = __ldg(reinterpret_cast<const uint2*>(dskip) + db * 16 + 128 + j);
                    sts128(sbase + DSK_OFF + j * 16, d0.x, d0.y, d1.x, d1.y);
                }
                float s = 0.f;
                #pragma unroll
                for (int i = 0; i < 16; i++) s += __ldcg(&g_gp[(16 * rc + i) * 128 + j]);
                const float gv = bf16r(__fdividef(1.f, 1.f + expf(-bf16r(s))));
                sts32(sbase + GATE_OFF + 4 * j, __float_as_uint(bf16r(1.f - gv)));
                gen_dft(sbase + R2, j, 16 * j + rc, 0, 8, gv * (1.f / 1048576.f), gv * (1.f / 1048576.f));
                const uint8_t* img = reinterpret_cast<const uint8_t*>(g_X2) + (8 * rc + db) * X2_IMG;
                mbar_wait(ZB, 0);
                if ((j >> 4) == 4) {
                    const float cs = g_img.cs[0][4 * rc][0], sn = g_img.cs[0][4 * rc][1];
                    const uint4* s4 = reinterpret_cast<const uint4*>(img + ((j >> 3) & 1) * (X2_IMG / 2) + 16384) + (j & 7);
                    const uint4 a = __ldcg(s4), b = __ldcg(s4 + 64);
                    sts128(sbase + R1 + ((j >> 3) & 1) * 16384 + 1024 + (j & 7) * 16,
                           pack2(cs * bflo(a.x) - sn * bflo(b.x), cs * bfhi(a.x) - sn * bfhi(b.x)), pack2(cs * bflo(a.y) - sn * bflo(b.y), cs * bfhi(a.y) - sn * bfhi(b.y)),
                           pack2(cs * bflo(a.z) - sn * bflo(b.z), cs * bfhi(a.z) - sn * bfhi(b.z)), pack2(cs * bflo(a.w) - sn * bflo(b.w), cs * bfhi(a.w) - sn * bfhi(b.w)));
                }
                fence_async();
                bar_arrive_n(ZBAR, 384);
                if (j == 0) DBG_STAMP(11);
            }
        }
      }
    } else {
        if (cta < 128) {
            float A[64];
            #pragma unroll
            for (int i = 0; i < 64; i++) A[i] = 0.f;
            gemm_main(A, wg, warp, lane);
            if (tid == 0) DBG_STAMP(12);
            const int ln = tid128() & 31, row = 64 * wg + 16 * warp + (ln >> 2);
            bar_sync_n(ZBAR, 384);
            mbar_wait(XB, 1);
            wgmma_wait<0>();
            reg_fence<64>(A);
            #pragma unroll
            for (int h = 0; h < 2; h++) {
                boundary();
                const float om = __uint_as_float(lds32(sbase + GATE_OFF + 4 * (row + 8 * h))), omh = 0.5f * om;
                const uint32_t xa = sbase + R0 + (row + 8 * h) * 128 + (ln & 1) * 8;
                #pragma unroll
                for (int J = 0; J < 4; J++) {
                    if (J == 2) boundary();
                    const uint32_t xo = xa + (((2 * J + ((ln >> 1) & 1)) ^ (ln >> 2)) << 4);
                    uint2 p = lds64(xo), s = lds64(xo + 16384);
                    const uint4 dk = lds128(sbase + DSK_OFF + (4 * J + (ln & 3)) * 16);
                    p.x = hmul2bf(p.x, dk.x); p.y = hmul2bf(p.y, dk.y); s.x = hmul2bf(s.x, dk.z); s.y = hmul2bf(s.y, dk.w);
                    float* a = A + 8 * J + 2 * h;
                    float u, v;
                    u = fmaf(om, a[0], omh * bflo(p.x)); v = fmaf(om, a[32], omh * bflo(s.x)); a[0] = u + v; a[32] = u - v;
                    u = fmaf(om, a[1], omh * bfhi(p.x)); v = fmaf(om, a[33], omh * bfhi(s.x)); a[1] = u + v; a[33] = u - v;
                    u = fmaf(om, a[4], omh * bflo(p.y)); v = fmaf(om, a[36], omh * bflo(s.y)); a[4] = u + v; a[36] = u - v;
                    u = fmaf(om, a[5], omh * bfhi(p.y)); v = fmaf(om, a[37], omh * bfhi(s.y)); a[5] = u + v; a[37] = u - v;
                }
            }
            if (tid == 0) DBG_STAMP(6);
            const uint32_t s16 = to16(sbase);
            wgmma_fence();
            #pragma unroll
            for (int ks = 0; ks < 8; ks++)
                ss128<0, 1>(A, mkd(s16 + wg * 512, R2 + (ks >> 2) * 16384 + (ks & 3) * 32, 16, 1024, 1), mkd(s16, R1 + ks * 2048, 16384, 1024, 1));
            wgmma_commit();
            float* o = out + (size_t)(16 * row + rc) * 1024 + db * 64 + 4 * (ln & 3);
            wgmma_wait<0>();
            reg_fence<64>(A);
            #pragma unroll
            for (int h = 0; h < 2; h++)
                #pragma unroll
                for (int J = 0; J < 4; J++) {
                    if (h + J > 0 && !(J & 1)) boundary();
                    const float* a = A + 8 * J + 2 * h;
                    __stcs(reinterpret_cast<float4*>(o + h * 131072 + J * 16), make_float4(a[0] + a[32], a[1] + a[33], a[4] + a[36], a[5] + a[37]));
                    __stcs(reinterpret_cast<float4*>(o + h * 131072 + J * 16 + 512), make_float4(a[0] - a[32], a[1] - a[33], a[4] - a[36], a[5] - a[37]));
                }
            if (tid == 0) DBG_STAMP(7);
        }
    }
}

typedef CUresult (*PFN_encodeTiled_t)(CUtensorMap*, CUtensorMapDataType, cuuint32_t, void*, const cuuint64_t*, const cuuint64_t*,
                                      const cuuint32_t*, const cuuint32_t*, CUtensorMapInterleave, CUtensorMapSwizzle,
                                      CUtensorMapL2promotion, CUtensorMapFloatOOBfill);

static void make_map(PFN_encodeTiled_t enc, CUtensorMap* m, int rank, const void* ptr, const cuuint64_t* dims, const cuuint64_t* strides, const cuuint32_t* box) {
    cuuint32_t es[5] = {1, 1, 1, 1, 1};
    enc(m, CU_TENSOR_MAP_DATA_TYPE_BFLOAT16, rank, (void*)ptr, dims, strides, box, es, CU_TENSOR_MAP_INTERLEAVE_NONE, CU_TENSOR_MAP_SWIZZLE_128B,
        CU_TENSOR_MAP_L2_PROMOTION_L2_128B, CU_TENSOR_MAP_FLOAT_OOB_FILL_NONE);
}
static void make_map_2d(PFN_encodeTiled_t enc, CUtensorMap* m, const void* ptr, int rows, int cols, int box_rows) {
    cuuint64_t dims[2] = {(cuuint64_t)cols, (cuuint64_t)rows};
    cuuint64_t strides[1] = {(cuuint64_t)cols * 2};
    cuuint32_t box[2] = {64, (cuuint32_t)box_rows};
    make_map(enc, m, 2, ptr, dims, strides, box);
}

extern "C" void kernel_launch(void* const* d_in, const int* in_sizes, int n_in, void* d_out, int out_size) {
    const __nv_bfloat16* x = (const __nv_bfloat16*)d_in[0];
    const __nv_bfloat16* w_r = (const __nv_bfloat16*)d_in[1];
    const __nv_bfloat16* w_i = (const __nv_bfloat16*)d_in[2];
    const __nv_bfloat16* lam_re = (const __nv_bfloat16*)d_in[4];
    const __nv_bfloat16* lam_im = (const __nv_bfloat16*)d_in[5];
    const __nv_bfloat16* B_re = (const __nv_bfloat16*)d_in[6];
    const __nv_bfloat16* B_im = (const __nv_bfloat16*)d_in[7];
    const __nv_bfloat16* C_re = (const __nv_bfloat16*)d_in[8];
    const __nv_bfloat16* C_im = (const __nv_bfloat16*)d_in[9];
    const __nv_bfloat16* log_dt = (const __nv_bfloat16*)d_in[10];
    const __nv_bfloat16* dskip = (const __nv_bfloat16*)d_in[11];
    const __nv_bfloat16* gate_w = (const __nv_bfloat16*)d_in[12];

    static PFN_encodeTiled_t enc = nullptr;
    static Maps mp;
    static int grid = 130;
    static const void* key[7] = {nullptr, nullptr, nullptr, nullptr, nullptr, nullptr, nullptr};
    if (!enc) {
        cudaDriverEntryPointQueryResult qres;
        cudaGetDriverEntryPoint("cuTensorMapEncodeTiled", (void**)&enc, cudaEnableDefault, &qres);
        cudaFuncSetAttribute(fused_kernel, cudaFuncAttributeMaxDynamicSharedMemorySize, TOT_SMEM);
        int dev = 0, nsm = 0;
        cudaGetDevice(&dev);
        cudaDeviceGetAttribute(&nsm, cudaDevAttrMultiProcessorCount, dev);
        grid = nsm == NCTA ? NCTA : 130;
    }
    if (key[0] != x || key[1] != B_re || key[2] != B_im || key[3] != C_re || key[4] != C_im || key[5] != w_r || key[6] != w_i) {
        make_map_2d(enc, &mp.Bre, B_re, P_DIM, D_DIM, 64);
        make_map_2d(enc, &mp.Bim, B_im, P_DIM, D_DIM, 64);
        make_map_2d(enc, &mp.X, x, S_LEN, D_DIM, 128);
        make_map_2d(enc, &mp.Xr, x, S_LEN / 16, D_DIM * 16, 32);
        {
            cuuint64_t dims[5] = {P_DIM, 2, 4, 2, D_DIM / 16};
            cuuint64_t strides[4] = {P_DIM * 2, P_DIM * 2 * 4, P_DIM * 2 * 2, P_DIM * 2 * 16};
            cuuint32_t box[5] = {64, 2, 4, 2, 4};
            make_map(enc, &mp.Cre, 5, C_re, dims, strides, box);
            make_map(enc, &mp.Cim, 5, C_im, dims, strides, box);
        }
        for (int a = 0; a < 2; a++) {
            cuuint64_t dims[3] = {128 * 513 - 448, 8, 16};
            cuuint64_t strides[2] = {128, 128 * 513 * 2};
            cuuint32_t box[3] = {64, 8, 8}, es[3] = {1, 1, 1};
            enc(&mp.W[a], CU_TENSOR_MAP_DATA_TYPE_BFLOAT16, 3, (void*)(a ? w_i : w_r), dims, strides, box, es, CU_TENSOR_MAP_INTERLEAVE_NONE, CU_TENSOR_MAP_SWIZZLE_128B,
                CU_TENSOR_MAP_L2_PROMOTION_L2_128B, CU_TENSOR_MAP_FLOAT_OOB_FILL_NONE);
        }
        key[5] = w_r; key[6] = w_i;
        key[0] = x; key[1] = B_re; key[2] = B_im; key[3] = C_re; key[4] = C_im;
    }
    fused_kernel<<<grid, 640, TOT_SMEM, cudaStreamPerThread>>>(mp, x, w_r, w_i, lam_re, lam_im, log_dt, dskip, gate_w, C_re, C_im, B_re, B_im,
        (float*)d_out, grid == NCTA ? NCTA : 0u);
}
```

```cpp
#include <cuda_runtime.h>
#include <cuda_bf16.h>
#include <cuda.h>
#include <stdint.h>

#define ABL 0
#define S_LEN 2048
#define D_DIM 1024
#define P_DIM 1024

namespace ct {
constexpr double PI = 3.14159265358979323846264338327950288;
constexpr double tsin(double x) { double term = x, sum = x; for (int i = 1; i < 12; i++) { term *= -x * x / ((2 * i) * (2 * i + 1)); sum += term; } return sum; }
constexpr double tcos(double x) { double term = 1, sum = 1; for (int i = 1; i < 12; i++) { term *= -x * x / ((2 * i - 1) * (2 * i)); sum += term; } return sum; }
struct CosTab { double v[513]; };
constexpr CosTab make_cos() {
    CosTab t{};
    for (int m = 0; m <= 512; m++) t.v[m] = m == 512 ? 0.0 : (m <= 256 ? tcos(2 * PI * m / 2048.0) : tsin(2 * PI * (512 - m) / 2048.0));
    return t;
}
constexpr CosTab COS = make_cos();
constexpr double cos2048(int m) {
    m &= 2047;
    if (m > 1024) m = 2048 - m;
    if (m > 512) return -COS.v[1024 - m];
    return COS.v[m];
}
constexpr double sin2048(int m) { return cos2048(m - 512); }
constexpr unsigned short bf16bits(double v) {
    if (v == 0.0) return 0;
    unsigned short s = 0;
    if (v < 0) { s = 0x8000; v = -v; }
    int e = 0;
    while (v >= 2.0) { v *= 0.5; e++; }
    while (v < 1.0) { v *= 2.0; e--; }
    double r = v * 128.0;
    int ri = (int)r;
    double fr = r - ri;
    if (fr > 0.5 || (fr == 0.5 && (ri & 1))) ri++;
    if (ri == 256) { ri = 128; e++; }
    return (unsigned short)(s | ((e + 127) << 7) | (ri - 128));
}
constexpr int kmaj(int row, int k, int sbo) { return ((row >> 3) * sbo + (k >> 3) * 128 + (row & 7) * 16 + (k & 7) * 2) >> 1; }
constexpr double rot(int ro, int ri, int a) { return ro == ri ? cos2048(a) : (ro == 0 ? sin2048(a) : -sin2048(a)); }
constexpr int bin(int n) { return (n & 8) | ((n & 3) << 1) | ((n >> 2) & 1); }
constexpr int bout(int n) { return ((n & 2) << 2) | ((n >> 1) & 6) | (n & 1); }
struct Half {
    unsigned short m4[4096];
    unsigned short b16i[1024];
    unsigned short tw[2][128][8];
};
struct Img { unsigned short b16f[1024]; Half h[2]; float cs[16][128][2]; unsigned short m4re[2][4096]; };
constexpr Img make_img() {
    Img t{};
    for (int n = 0; n < 32; n++) for (int k = 0; k < 32; k++) t.b16f[kmaj(n, k, 512)] = bf16bits(rot(((n >> 4) ^ (n >> 3)) & 1, k >> 4, bin(k & 15) * (n & 15) * 128));
    for (int r = 0; r < 16; r++) for (int j = 0; j < 128; j++) { t.cs[r][j][0] = (float)cos2048(16 * j + r); t.cs[r][j][1] = (float)sin2048(16 * j + r); }
    for (int ke = 0; ke < 2; ke++) {
        Half& h = t.h[ke];
        for (int n = 0; n < 32; n++) for (int k = 0; k < 32; k++) h.b16i[kmaj(n, k, 512)] = bf16bits(rot(n >> 4, ((k >> 4) ^ (k >> 3)) & 1, -bout(n & 15) * (k & 15) * 128));
        for (int m = 0; m < 64; m++) for (int k = 0; k < 64; k++) {
            int a = 4 * (m >> 3) + (m & 3), ro = (m >> 2) & 1, kx = 8 * (k >> 4) + (k & 7), ri = (k >> 3) & 1;
            h.m4[kmaj(m, k, 1024)] = bf16bits(rot(ro, ri, -a * (ke + 2 * kx) * 32));
            t.m4re[ke][kmaj(m, k, 1024)] = ro ? 0 : h.m4[kmaj(m, k, 1024)];
        }
        for (int tid = 0; tid < 128; tid++) {
            int kap = ke + 2 * (tid >> 2), q = tid & 3;
            for (int hb = 0; hb < 2; hb++) for (int e = 0; e < 2; e++) {
                int n = 8 * hb + 2 * q + e;
                h.tw[0][tid][4 * hb + e] = bf16bits(cos2048(2 * bin(n) * kap));  h.tw[0][tid][4 * hb + 2 + e] = bf16bits(-sin2048(2 * bin(n) * kap));
                h.tw[1][tid][4 * hb + e] = bf16bits(cos2048(2 * bout(n) * kap)); h.tw[1][tid][4 * hb + 2 + e] = bf16bits(sin2048(2 * bout(n) * kap));
            }
        }
    }
    return t;
}
}
__device__ __align__(128) const ct::Img g_img = ct::make_img();

#define RING 4
#define STGB 32768
#define R0 (4 * 32768)
#define R1 (5 * 32768)
#define R2 (6 * 32768)
#define B16F_OFF (7 * 32768)
#define BAR_OFF (B16F_OFF + 2048)
#define GATE_OFF (BAR_OFF + 256)
#define DSK_OFF (GATE_OFF + 512)
#define TOT_SMEM (DSK_OFF + 256)
#define NCTA 132
#define X2_IMG 36864

__device__ __align__(1024) uint4 g_X1[128 * 2048];
__device__ __align__(1024) uint4 g_X2[128 * X2_IMG / 16];
__device__ __align__(128) float g_gp[256 * 128];
__device__ __align__(1024) uint4 g_h[16 * 32 * 1024];
__device__ __align__(128) unsigned long long g_agg[16 * P_DIM];
__device__ __align__(128) unsigned int g_cnt[8 * 32];
#define g_ticket g_cnt[0]
#define g_cnt1 g_cnt[32]
#define g_cnt2 g_cnt[64]
#define g_cnt3 g_cnt[224]
#define g_cnth(i) g_cnt[96 + 32 * (i)]

#define DBG_END
#define DBG_STAMP(slot)
#define DBG_RAW(slot, v)

__device__ __forceinline__ float bf16r(float v) { return __bfloat162float(__float2bfloat16_rn(v)); }
__device__ __forceinline__ float2 cmul(float2 a, float2 b) { return make_float2(a.x * b.x - a.y * b.y, a.x * b.y + a.y * b.x); }
__device__ __forceinline__ float2 cfma(float2 a, float2 b, float2 c) {
    float re = fmaf(a.x, b.x, c.x); re = fmaf(-a.y, b.y, re);
    float im = fmaf(a.x, b.y, c.y); im = fmaf(a.y, b.x, im);
    return make_float2(re, im);
}
__device__ __forceinline__ uint32_t smem_u32(const void* p) { return (uint32_t)__cvta_generic_to_shared(p); }
__device__ __forceinline__ void bar_sync_n(int id, int n) { asm volatile("bar.sync %0, %1;" :: "r"(id), "r"(n) : "memory"); }
__device__ __forceinline__ void bar_arrive_n(int id, int n) { asm volatile("bar.arrive %0, %1;" :: "r"(id), "r"(n) : "memory"); }
__device__ __forceinline__ uint32_t pack2(float lo, float hi) { uint32_t r; asm("cvt.rn.bf16x2.f32 %0, %1, %2;" : "=r"(r) : "f"(hi), "f"(lo)); return r; }
__device__ __forceinline__ uint64_t mkd(uint32_t b16, uint32_t off, uint32_t lbo, uint32_t sbo, uint32_t swz = 0) {
    uint64_t d;
    asm("mov.b64 %0, {%1, %2};" : "=l"(d) : "r"(b16 + ((off >> 4) + ((lbo >> 4) << 16))), "r"((sbo >> 4) | (swz << 30)));
    return d;
}
__device__ __forceinline__ uint32_t to16(uint32_t saddr) { return 0x40; }
__device__ __forceinline__ void wgmma_fence() { asm volatile("wgmma.fence.sync.aligned;" ::: "memory"); }
__device__ __forceinline__ void wgmma_commit() { asm volatile("wgmma.commit_group.sync.aligned;" ::: "memory"); }
template <int N> __device__ __forceinline__ void wgmma_wait() { asm volatile("wgmma.wait_group.sync.aligned %0;" :: "n"(N) : "memory"); }
__device__ __forceinline__ void fence_async() { asm volatile("fence.proxy.async.shared::cta;" ::: "memory"); }
template <int N> __device__ __forceinline__ void reg_fence(float* d) {
    #pragma unroll
    for (int i = 0; i < N; i++) asm volatile("" : "+f"(d[i]) :: "memory");
}
#define X16(c, d, o) c(d[o]),c(d[o+1]),c(d[o+2]),c(d[o+3]),c(d[o+4]),c(d[o+5]),c(d[o+6]),c(d[o+7]),c(d[o+8]),c(d[o+9]),c(d[o+10]),c(d[o+11]),c(d[o+12]),c(d[o+13]),c(d[o+14]),c(d[o+15])
#define RW(x) "+f"(x)
#define WO(x) "=f"(x)
#define R64(d) X16(RW, d, 0), X16(RW, d, 16), X16(RW, d, 32), X16(RW, d, 48)
#define W64(d) X16(WO, d, 0), X16(WO, d, 16), X16(WO, d, 32), X16(WO, d, 48)
#define R32(d) X16(RW, d, 0), X16(RW, d, 16)
#define W32(d) X16(WO, d, 0), X16(WO, d, 16)
#define R16(d) X16(RW, d, 0)
#define WO16(d) X16(WO, d, 0)
#define L64 "{%0,%1,%2,%3,%4,%5,%6,%7,%8,%9,%10,%11,%12,%13,%14,%15,%16,%17,%18,%19,%20,%21,%22,%23,%24,%25,%26,%27,%28,%29,%30,%31," \
        "%32,%33,%34,%35,%36,%37,%38,%39,%40,%41,%42,%43,%44,%45,%46,%47,%48,%49,%50,%51,%52,%53,%54,%55,%56,%57,%58,%59,%60,%61,%62,%63}"
#define L32 "{%0,%1,%2,%3,%4,%5,%6,%7,%8,%9,%10,%11,%12,%13,%14,%15,%16,%17,%18,%19,%20,%21,%22,%23,%24,%25,%26,%27,%28,%29,%30,%31}"
#define L16 "{%0,%1,%2,%3,%4,%5,%6,%7,%8,%9,%10,%11,%12,%13,%14,%15}"

template <int TA, int TB> __device__ __forceinline__ void ss128(float* d, uint64_t a, uint64_t b) {
    asm volatile("wgmma.mma_async.sync.aligned.m64n128k16.f32.bf16.bf16 " L64 ", %64, %65, 1, 1, 1, %66, %67;\n" : R64(d) : "l"(a), "l"(b), "n"(TA), "n"(TB));
}
template <int TA, int TB> __device__ __forceinline__ void ss128_p(float* d, uint64_t a, uint64_t b, int acc) {
    asm volatile("{\n.reg .pred p;\nsetp.ne.s32 p, %68, 0;\nwgmma.mma_async.sync.aligned.m64n128k16.f32.bf16.bf16 " L64 ", %64, %65, p, 1, 1, %66, %67;\n}\n" : R64(d) : "l"(a), "l"(b), "n"(TA), "n"(TB), "r"(acc));
}
template <int TA, int TB> __device__ __forceinline__ void ss128_z(float* d, uint64_t a, uint64_t b) {
    asm volatile("wgmma.mma_async.sync.aligned.m64n128k16.f32.bf16.bf16 " L64 ", %64, %65, 0, 1, 1, %66, %67;\n" : W64(d) : "l"(a), "l"(b), "n"(TA), "n"(TB));
}
__device__ __forceinline__ void rs64(float* d, uint4 a, uint64_t b) {
    asm volatile("wgmma.mma_async.sync.aligned.m64n64k16.f32.bf16.bf16 " L32 ", {%32,%33,%34,%35}, %36, 1, 1, 1, 0;\n" : R32(d) : "r"(a.x), "r"(a.y), "r"(a.z), "r"(a.w), "l"(b));
}
__device__ __forceinline__ void rs64_z(float* d, uint4 a, uint64_t b) {
    asm volatile("wgmma.mma_async.sync.aligned.m64n64k16.f32.bf16.bf16 " L32 ", {%32,%33,%34,%35}, %36, 0, 1, 1, 0;\n" : W32(d) : "r"(a.x), "r"(a.y), "r"(a.z), "r"(a.w), "l"(b));
}
__device__ __forceinline__ void rs32(float* d, uint32_t a0, uint32_t a1, uint32_t a2, uint32_t a3, uint64_t b) {
    asm volatile("wgmma.mma_async.sync.aligned.m64n32k16.f32.bf16.bf16 " L16 ", {%16,%17,%18,%19}, %20, 1, 1, 1, 0;\n"
        : R16(d) : "r"(a0), "r"(a1), "r"(a2), "r"(a3), "l"(b));
}
__device__ __forceinline__ void rs32_z(float* d, uint32_t a0, uint32_t a1, uint32_t a2, uint32_t a3, uint64_t b) {
    asm volatile("wgmma.mma_async.sync.aligned.m64n32k16.f32.bf16.bf16 " L16 ", {%16,%17,%18,%19}, %20, 0, 1, 1, 0;\n"
        : WO16(d) : "r"(a0), "r"(a1), "r"(a2), "r"(a3), "l"(b));
}
__device__ __forceinline__ void stsm_x4(uint32_t addr, uint32_t r0, uint32_t r1, uint32_t r2, uint32_t r3) {
    asm volatile("stmatrix.sync.aligned.m8n8.x4.shared.b16 [%0], {%1, %2, %3, %4};" :: "r"(addr), "r"(r0), "r"(r1), "r"(r2), "r"(r3) : "memory");
}
__device__ __forceinline__ uint32_t lds32(uint32_t a) { uint32_t v; asm volatile("ld.shared.u32 %0, [%1];" : "=r"(v) : "r"(a) : "memory"); return v; }
__device__ __forceinline__ uint2 lds64(uint32_t a) { uint2 v; asm volatile("ld.shared.v2.u32 {%0, %1}, [%2];" : "=r"(v.x), "=r"(v.y) : "r"(a) : "memory"); return v; }
__device__ __forceinline__ uint4 lds128(uint32_t a) { uint4 v; asm volatile("ld.shared.v4.u32 {%0, %1, %2, %3}, [%4];" : "=r"(v.x), "=r"(v.y), "=r"(v.z), "=r"(v.w) : "r"(a) : "memory"); return v; }
__device__ __forceinline__ void sts32(uint32_t a, uint32_t x) { asm volatile("st.shared.u32 [%0], %1;" :: "r"(a), "r"(x) : "memory"); }
__device__ __forceinline__ void sts128(uint32_t a, uint32_t x, uint32_t y, uint32_t z, uint32_t w) {
    asm volatile("st.shared.v4.u32 [%0], {%1, %2, %3, %4};" :: "r"(a), "r"(x), "r"(y), "r"(z), "r"(w) : "memory");
}
__device__ __forceinline__ float bflo(uint32_t v) { return __uint_as_float(v << 16); }
__device__ __forceinline__ float bfhi(uint32_t v) { return __uint_as_float(v & 0xffff0000u); }
__device__ __forceinline__ uint32_t hmul2bf(uint32_t a, uint32_t b) { uint32_t r; asm("mul.rn.bf16x2 %0, %1, %2;" : "=r"(r) : "r"(a), "r"(b)); return r; }
__device__ __forceinline__ uint32_t hadd2bf(uint32_t a, uint32_t b) { uint32_t r; asm("add.rn.bf16x2 %0, %1, %2;" : "=r"(r) : "r"(a), "r"(b)); return r; }
__device__ __forceinline__ uint32_t hsub2bf(uint32_t a, uint32_t b) { uint32_t r; asm("sub.rn.bf16x2 %0, %1, %2;" : "=r"(r) : "r"(a), "r"(b)); return r; }
__device__ __forceinline__ void mbar_init(uint32_t a, uint32_t c) { asm volatile("mbarrier.init.shared.b64 [%0], %1;" :: "r"(a), "r"(c)); }
__device__ __forceinline__ void mbar_wait(uint32_t a, uint32_t ph) {
    asm volatile("{\n.reg .pred p;\n.reg .u32 n;\nmov.u32 n, 0;\nWAIT_LOOP:\nmbarrier.try_wait.parity.shared.b64 p, [%0], %1;\n@p bra DONE;\nadd.u32 n, n, 1;\nsetp.lt.u32 p, n, 4000000;\n@p bra WAIT_LOOP;\nDONE:\n}" :: "r"(a), "r"(ph) : "memory");
}
__device__ __forceinline__ void mbar_wait_n(uint32_t a, uint32_t ph, uint32_t& n) {
    asm volatile("{\n.reg .pred p;\nWAIT_LOOP:\nmbarrier.try_wait.parity.shared.b64 p, [%1], %2;\n@p bra DONE;\nadd.u32 %0, %0, 1;\nsetp.lt.u32 p, %0, 4000000;\n@p bra WAIT_LOOP;\nDONE:\n}" : "+r"(n) : "r"(a), "r"(ph) : "memory");
}
__device__ __forceinline__ bool mbar_test(uint32_t a, uint32_t ph) {
    uint32_t r;
    asm volatile("{\n.reg .pred p;\nmbarrier.test_wait.parity.shared.b64 p, [%1], %2;\nselp.u32 %0, 1, 0, p;\n}" : "=r"(r) : "r"(a), "r"(ph) : "memory");
    return __all_sync(0xffffffffu, r != 0);
}
__device__ __forceinline__ void mbar_expect_tx(uint32_t a, uint32_t bytes) { asm volatile("mbarrier.arrive.expect_tx.shared.b64 _, [%0], %1;" :: "r"(a), "r"(bytes) : "memory"); }
__device__ __forceinline__ void mbar_arrive(uint32_t a) { asm volatile("mbarrier.arrive.shared.b64 _, [%0];" :: "r"(a) : "memory"); }
__device__ __forceinline__ void mbar_arrive2(uint32_t a) { asm volatile("mbarrier.arrive.shared.b64 _, [%0], 2;" :: "r"(a) : "memory"); }
__device__ __forceinline__ void tma_load_2d(uint32_t dst, const CUtensorMap* map, int c0, int c1, uint32_t bar) {
    asm volatile("cp.async.bulk.tensor.2d.shared::cluster.global.mbarrier::complete_tx::bytes [%0], [%1, {%3, %4}], [%2];"
        :: "r"(dst), "l"(map), "r"(bar), "r"(c0), "r"(c1) : "memory");
}
__device__ __forceinline__ void tma_load_5d(uint32_t dst, const CUtensorMap* map, int c0, int c4, uint32_t bar) {
    asm volatile("cp.async.bulk.tensor.5d.shared::cluster.global.mbarrier::complete_tx::bytes [%0], [%1, {%3, %5, %5, %5, %4}], [%2];"
        :: "r"(dst), "l"(map), "r"(bar), "r"(c0), "r"(c4), "r"(0) : "memory");
}
__device__ __forceinline__ void bulk_load(uint32_t dst, const void* src, uint32_t bytes, uint32_t bar) {
    asm volatile("cp.async.bulk.shared::cluster.global.mbarrier::complete_tx::bytes [%0], [%1], %2, [%3];" :: "r"(dst), "l"(src), "r"(bytes), "r"(bar) : "memory");
}
__device__ __forceinline__ void l2_prefetch(const void* p, uint32_t bytes) {
    asm volatile("cp.async.bulk.prefetch.L2.global [%0], %1;" :: "l"(p), "r"(bytes) : "memory");
}
__device__ __forceinline__ void wait_counter(const unsigned int* p, unsigned int target) {
    unsigned int cur; int spins = 0;
    #pragma unroll 1
    do {
        asm volatile("ld.relaxed.gpu.global.u32 %0, [%1];" : "=r"(cur) : "l"(p) : "memory");
        if ((int)(cur - target) >= 0) break;
        __nanosleep(20);
    } while (++spins < (1 << 22));
}
__device__ __forceinline__ void red_release(unsigned int* p) { asm volatile("red.release.gpu.global.add.u32 [%0], 1;" :: "l"(p) : "memory"); }
__device__ __forceinline__ uint32_t clk32() { uint32_t c; asm volatile("mov.u32 %0, %%clock;" : "=r"(c)); return c; }
__device__ __forceinline__ bool elect_one() {
    uint32_t r;
    asm volatile("{\n.reg .pred p;\nelect.sync _|p, 0xffffffff;\nselp.u32 %0, 1, 0, p;\n}" : "=r"(r));
    return r != 0;
}
#define PAUSE_NS 0
__device__ __forceinline__ void pause() { __nanosleep(PAUSE_NS); }
__device__ __forceinline__ int tid128() { int t; asm volatile("mov.u32 %0, %%tid.x;" : "=r"(t)); return t & 127; }
#define CTW(yr, yi, qx, qy) do { const float _r = (yr), _i = (yi); yr = _r * (qx) - _i * (qy); yi = _r * (qy) + _i * (qx); } while (0)
typedef __nv_bfloat162 bf2;
__device__ __forceinline__ bf2 asbf2(uint32_t v) { return *reinterpret_cast<bf2*>(&v); }
__device__ __forceinline__ uint32_t asu32(bf2 v) { return *reinterpret_cast<uint32_t*>(&v); }
template <int M> struct W16 { static constexpr uint32_t c = ct::bf16bits(ct::cos2048(128 * M)) * 0x10001u, s = ct::bf16bits(-ct::sin2048(128 * M)) * 0x10001u; };
__device__ __forceinline__ void pin(bf2& v) { uint32_t u = asu32(v); asm volatile("" : "+r"(u) :: "memory"); v = asbf2(u); }
__device__ __forceinline__ bf2 neg2(bf2 v) { return asbf2(asu32(v) ^ 0x80008000u); }
__device__ __forceinline__ void cmul2(bf2& r, bf2& i, bf2 wr, bf2 wi) {
    const bf2 a = r, b = i;
    r = __hfma2(a, wr, __hmul2(b, neg2(wi))); i = __hfma2(b, wr, __hmul2(a, wi));
}
__device__ __forceinline__ void bfly4(bf2* r, bf2* i, int o, int s) {
    const bf2 ar = __hadd2(r[o], r[o + 2 * s]), ai = __hadd2(i[o], i[o + 2 * s]), br = __hsub2(r[o], r[o + 2 * s]), bi = __hsub2(i[o], i[o + 2 * s]);
    const bf2 cr = __hadd2(r[o + s], r[o + 3 * s]), ci = __hadd2(i[o + s], i[o + 3 * s]), dr = __hsub2(r[o + s], r[o + 3 * s]), di = __hsub2(i[o + s], i[o + 3 * s]);
    r[o] = __hadd2(ar, cr); i[o] = __hadd2(ai, ci); r[o + 2 * s] = __hsub2(ar, cr); i[o + 2 * s] = __hsub2(ai, ci);
    r[o + s] = __hadd2(br, di); i[o + s] = __hsub2(bi, dr); r[o + 3 * s] = __hsub2(br, di); i[o + 3 * s] = __hadd2(bi, dr);
}
template <int M> __device__ __forceinline__ void tw16(bf2& r, bf2& i) {
    if (M == 4) { const bf2 a = r; r = i; i = neg2(a); }
    else cmul2(r, i, asbf2(W16<M>::c), asbf2(W16<M>::s));
}
__device__ __forceinline__ void tw16_all(bf2* r, bf2* i) {
    tw16<1>(r[5], i[5]); tw16<2>(r[6], i[6]); tw16<3>(r[7], i[7]); tw16<2>(r[9], i[9]); tw16<4>(r[10], i[10]); tw16<6>(r[11], i[11]);
    tw16<3>(r[13], i[13]); tw16<6>(r[14], i[14]); tw16<9>(r[15], i[15]);
}

__device__ __forceinline__ void dft16(bf2* r, bf2* i) {
    #pragma unroll
    for (int r0 = 0; r0 < 4; r0++) bfly4(r, i, r0, 4);
    tw16_all(r, i);
    #pragma unroll
    for (int k1 = 0; k1 < 4; k1++) bfly4(r, i, 4 * k1, 1);
}
__device__ __forceinline__ void idft16(bf2* r, bf2* i) {
    #pragma unroll
    for (int k1 = 0; k1 < 4; k1++) bfly4(i, r, 4 * k1, 1);
    tw16_all(i, r);
    #pragma unroll
    for (int r0 = 0; r0 < 4; r0++) bfly4(i, r, r0, 4);
}

#define DBAR 1
#define FBAR 2
#define SBAR 3
#define HBAR 6
#define WBAR 4
#define ZBAR 5
#define FULL(s) (bars + 8 * (s))
#define EMPTY(s) (bars + 8 * (RING + (s)))
#define XB (bars + 64)
#define X1B (bars + 72)
#define WQ(i) (bars + 144 + 8 * (i))
#define ZB (bars + 88)
#define EPB (bars + 96)
#define R0F (bars + 104)
#define HOK(i) (bars + 112 + 8 * (i))
#define EPO_OFF (BAR_OFF + 160)
#define ROLE_OFF (BAR_OFF + 164)
#define SACT_OFF (BAR_OFF + 176)
#define LBAR 12
#define PSZ 8192
#define BND 2
#define PHOLD 0
#define PBAR 0
#define X1C (bars + 168)
#define PC1M 256
#define P1END 10500
#define LAM_OFF (R2 + 27648)
#define PCW3 100
#define PCW 300
#define PT_OFF (R2 + 26624)
#define WBUF(i) ((i) == 1 ? R1 : ((i) == 2 ? R1 + 16384 : R2 + 10240))
#define PC1 512
#define PC2 88
#define PCH 96
#define PCL 100
__device__ __forceinline__ void delay(int cycles) { if (cycles > 0) { const uint32_t c = clk32(); while ((int)(clk32() - c) < cycles) { } } }
__device__ __forceinline__ void pace(uint32_t& t, int cycles) { if (cycles == 0) return; while ((int)(clk32() - t) < 0) { } t += cycles; }
__device__ __forceinline__ void pf_line(const void* p) { asm volatile("prefetch.global.L2 [%0];" :: "l"(p)); }

__device__ __forceinline__ float2 cis(int m) { return __ldg(reinterpret_cast<const float2*>(g_img.cs[m & 15][(m >> 4) & 127])); }
__device__ __forceinline__ void gen_dft(uint32_t dst, int j, int t, int b0, int b1, float scale, float c0) {
    const float c2 = 2.f * cis(t).x;
    float2 a = cis(t - 8 * b0 * t), b = cis(-8 * b0 * t);
    a.x *= scale; a.y *= scale; b.x *= scale; b.y *= scale;
    float2 z0 = b0 ? b : make_float2(c0, (j & 1) ? -c0 : c0);
    dst += j * 128;
    #pragma unroll 1
    for (int blk = b0; blk < b1; blk++) {
        float2 v[9];
        v[0] = b;
        v[1] = make_float2(fmaf(c2, b.x, -a.x), fmaf(c2, b.y, -a.y));
        #pragma unroll
        for (int k = 2; k < 9; k++) v[k] = make_float2(fmaf(c2, v[k - 1].x, -v[k - 2].x), fmaf(c2, v[k - 1].y, -v[k - 2].y));
        const uint32_t p = dst + (blk >> 2) * 16384, c = (2 * (blk & 3)) ^ (j & 7);
        sts128(p + c * 16, pack2(z0.x, v[1].x), pack2(v[2].x, v[3].x), pack2(v[4].x, v[5].x), pack2(v[6].x, v[7].x));
        sts128(p + (c ^ 1) * 16, pack2(z0.y, v[1].y), pack2(v[2].y, v[3].y), pack2(v[4].y, v[5].y), pack2(v[6].y, v[7].y));
        a = v[7]; b = v[8]; z0 = b;
    }
}

__device__ __forceinline__ void fft_p1(uint32_t sbase, int tile, int r, int db, uint32_t t_end) {
    const uint32_t s16 = to16(sbase);
    float acc[64];
    wgmma_fence();
    ss128_z<1, 1>(acc, mkd(s16 + tile * 1024, R1, 16384, 1024, 1), mkd(s16, R0, 16384, 1024, 1));
    #pragma unroll
    for (int ks = 1; ks < 8; ks++) ss128<1, 1>(acc, mkd(s16 + tile * 1024, R1 + ks * 2048, 16384, 1024, 1), mkd(s16, R0 + ks * 2048, 16384, 1024, 1));
    wgmma_commit();
    const int tid = tid128();
    float g0 = 0.f;
    uint4* dst = g_X1 + (64 * tile + 2 * (tid >> 2)) * 2048 + (r >> 3) * 1024 + db * 128 + (r & 7) * 16 + (tid & 3);
    wgmma_wait<0>();
    reg_fence<64>(acc);
    if (tid == 0) DBG_STAMP(116 + tile);
    if (PHOLD) bar_arrive_n(PBAR, 512);
    uint32_t tp = clk32();
    const int dt = min(max((int)(t_end - tp) >> 3, PC1M), PC1);
    tp += (threadIdx.x >> 5 & 7) * (dt >> 3);
    #pragma unroll
    for (int c = 0; c < 4; c++) {
        const float* u = acc + 4 * (c >> 1) + (c & 1);
        #pragma unroll
        for (int ke = 0; ke < 2; ke++) {
            float v[8];
            #pragma unroll
            for (int z = 0; z < 8; z++) { const int ix = 8 * (z & 3) + 2 * (z >> 2); v[z] = ke ? u[ix] - u[ix + 32] : u[ix] + u[ix + 32]; }
            const uint4 x = lds128(sbase + R0 + tile * 16384 + tid * 128 + (((2 * c + ke) ^ (tid & 7)) << 4)), gv = lds128(sbase + GATE_OFF + tile * 128 + (2 * c + ke) * 16);
            uint4 o = make_uint4(pack2(v[0], v[1]), pack2(v[2], v[3]), pack2(v[4], v[5]), pack2(v[6], v[7]));
            asm volatile("" : "+r"(o.x), "+r"(o.y), "+r"(o.z), "+r"(o.w) :: "memory");
            pace(tp, dt);
            __stcg(dst + ke * 2048 + 4 * c, o);
            const uint32_t p0 = hmul2bf(x.x, gv.x), p1 = hmul2bf(x.y, gv.y), p2 = hmul2bf(x.z, gv.z), p3 = hmul2bf(x.w, gv.w);
            g0 += ((bflo(p0) + bfhi(p0)) + (bflo(p1) + bfhi(p1))) + ((bflo(p2) + bfhi(p2)) + (bflo(p3) + bfhi(p3)));
        }
    }
    __stcg(&g_gp[(16 * r + 2 * db + tile) * 128 + tid], g0);
}

__device__ __forceinline__ int w_first(int unit, int hb) { const int ka = unit >> 1, ke = unit & 1; return hb ? ((128 - ka) & 127) * 513 + 2 - ke : ka * 513 + ke; }
__device__ __forceinline__ void load_w(const CUtensorMap* wm, uint32_t sbase, int unit, int i) {
    const uint32_t bars = sbase + BAR_OFF;
    mbar_expect_tx(WQ(i >> 1), 16384);
    #pragma unroll 1
    for (int a = 0; a < 4; a++) {
        asm volatile("cp.async.bulk.tensor.3d.shared::cluster.global.mbarrier::complete_tx::bytes [%0], [%1, {%3, %4, %5}], [%2];"
            :: "r"(sbase + WBUF(i) + a * 4096), "l"(wm + (i & 1)), "r"(WQ(i >> 1)), "r"(w_first(unit, i >> 1) & ~15), "r"(0), "r"(4 * a) : "memory");
        delay(i == 3 ? PCW3 : PCW);
    }
}
__device__ __forceinline__ uint32_t w_off(int e) { e &= 511; return (e >> 6) * 128 + ((((e >> 3) ^ (e >> 6)) & 7) << 4) + (e & 7) * 2; }
__device__ __forceinline__ void sts16(uint32_t a, uint32_t v) { asm volatile("st.shared.u16 [%0], %1;" :: "r"(a), "h"((unsigned short)v) : "memory"); }
__device__ __forceinline__ void load_paced(uint32_t dst, const uint8_t* src, int n, uint32_t bar) {
    #pragma unroll 1
    for (int i = 0; i < n; i++) { bulk_load(dst + i * PSZ, src + i * PSZ, PSZ, bar); delay(PCL); }
}
__device__ __forceinline__ void boundary() { while (clk32() == 0) { } asm volatile("" ::: "memory"); }
__device__ __forceinline__ void yield_to_scan(uint32_t sbase) {
    #pragma unroll 1
    for (int n = 0; n < 100000 && lds32(sbase + SACT_OFF); n++) __nanosleep(50);
}
template <int OFF> __device__ __forceinline__ uint32_t lds_w(uint32_t a, uint32_t b) {
    uint32_t l, h;
    asm volatile("ld.shared.u16 %0, [%2 + %4];\nld.shared.u16 %1, [%3 + %4];" : "=r"(l), "=r"(h) : "r"(a), "r"(b), "n"(OFF) : "memory");
    return __byte_perm(l, h, 0x5410);
}
template <int S> __device__ __forceinline__ void load_ws(uint32_t* w, uint32_t a, uint32_t b) {
    if constexpr (S < 16) { w[S] = lds_w<((S >> 2) + 4 * (S & 3)) * 1024>(a, b); load_ws<S + 1>(w, a, b); }
}
template <int TB> __device__ __forceinline__ void ss64(float* d, uint64_t a, uint64_t b) {
    asm volatile("wgmma.mma_async.sync.aligned.m64n64k16.f32.bf16.bf16 " L32 ", %32, %33, 1, 1, 1, 0, %34;\n" : R32(d) : "l"(a), "l"(b), "n"(TB));
}
template <int TB> __device__ __forceinline__ void ss64_z(float* d, uint64_t a, uint64_t b) {
    asm volatile("wgmma.mma_async.sync.aligned.m64n64k16.f32.bf16.bf16 " L32 ", %32, %33, 0, 1, 1, 0, %34;\n" : W32(d) : "l"(a), "l"(b), "n"(TB));
}

__device__ __forceinline__ void fft_p2(uint32_t sbase, uint32_t bars, int unit, const __nv_bfloat16* w_r, const __nv_bfloat16* w_i) {
    const uint32_t s16 = to16(sbase);
    const ct::Half* tb = &g_img.h[unit & 1];
    uint32_t P[16][4];
    {
        const int tid = tid128();
        uint32_t sp = 0, pt[2] = {0, 0};
        const uint4 t = __ldg(reinterpret_cast<const uint4*>(tb->tw[0][tid]));
        if (tid < 32 && !(unit & 1)) {
            const int k1 = ((tid & 16) ? (128 - (unit >> 1)) & 127 : unit >> 1) + 128 * (tid & 15), o1 = k1 * 513 + 32 * (tid & 16), o2 = ((2048 - k1) & 2047) * 513 + 32 * (tid & 16);
            sp = pack2(0.5f * (__bfloat162float(w_r[o1]) + __bfloat162float(w_r[o2])), 0.5f * (__bfloat162float(w_i[o1]) - __bfloat162float(w_i[o2])));
        }
        #pragma unroll
        for (int hb = 0; hb < 2; hb++) {
            const int e0 = w_first(unit, hb), z = (e0 & 1) + 2 * (tid & 7), o = (tid >> 3) * 65664 + (e0 & ~15) + 512 + z;
            if (z + 2 <= (e0 & 15)) pt[hb] = reinterpret_cast<const unsigned short*>(w_r)[o] | ((uint32_t)reinterpret_cast<const unsigned short*>(w_i)[o] << 16);
        }
        sts32(sbase + PT_OFF + 4 * tid, pt[0]); sts32(sbase + PT_OFF + 512 + 4 * tid, pt[1]);
        mbar_wait(X1B, 0);
        if (tid < 32) sts32(sbase + DSK_OFF + 4 * tid, sp);
        if (unit >= 128) {
            mbar_wait(X1C, 0);
            #pragma unroll 1
            for (int i = 0; i < 16; i++) {
                const float2 w = cis(-64 * ((i & 8) + (tid >> 4)));
                const uint32_t a = sbase + R1 + (i * 128 + tid) * 16;
                const uint2 v = lds64(a + 8);
                sts128(a, pack2(bflo(v.x) * w.x, bfhi(v.x) * w.x), pack2(bflo(v.y) * w.x, bfhi(v.y) * w.x), pack2(bflo(v.x) * w.y, bfhi(v.x) * w.y), pack2(bflo(v.y) * w.y, bfhi(v.y) * w.y));
            }
            fence_async();
            bar_sync_n(FBAR, 128);
        }
        if (tid == 0) DBG_STAMP(17);
        #pragma unroll
        for (int h = 0; h < 2; h++) {
            float acc[64];
            if (h) mbar_wait(X1C, 0);
            wgmma_fence();
            ss128_z<1, 0>(acc, mkd(s16, R2, 1024, 128), mkd(s16, R1 + h * 16384, 2048, 128));
            #pragma unroll
            for (int s = 1; s < 4; s++) ss128<1, 0>(acc, mkd(s16, R2 + s * 2048, 1024, 128), mkd(s16, R1 + h * 16384 + s * 4096, 2048, 128));
            wgmma_commit();
            wgmma_wait<0>();
            reg_fence<64>(acc);
            bar_arrive_n(LBAR + h, 160);
            bf2 f[32];
            #pragma unroll
            for (int z = 0; z < 32; z++) { uint32_t u = pack2(acc[2 * z], acc[2 * z + 1]); asm volatile("" : "+r"(u) :: "memory"); f[z] = asbf2(u); }
            boundary();
            float d[2][16];
            #pragma unroll
            for (int pr = 0; pr < 5; pr++) {
                if (pr == 2) boundary();
                if (pr < 4) {
                    bf2* a = f + 8 * pr;
                    #pragma unroll
                    for (int z = 0; z < 8; z++) pin(a[z]);
                    #pragma unroll
                    for (int z = 0; z < 4; z++) cmul2(a[2 * z], a[2 * z + 1], asbf2((z & 1) ? t.z : t.x), asbf2((z & 1) ? t.w : t.y));
                    wgmma_fence();
                    rs32_z(d[pr & 1], asu32(a[0]), asu32(a[4]), asu32(a[2]), asu32(a[6]), mkd(s16, B16F_OFF, 128, 512));
                    rs32(d[pr & 1], asu32(a[1]), asu32(a[5]), asu32(a[3]), asu32(a[7]), mkd(s16, B16F_OFF + 256, 128, 512));
                    wgmma_commit();
                }
                if (pr > 0) {
                    if (pr < 4) wgmma_wait<1>(); else wgmma_wait<0>();
                    reg_fence<16>(d[(pr - 1) & 1]);
                    #pragma unroll
                    for (int z = 0; z < 8; z++) {
                        uint32_t& p = P[8 * h + 2 * pr - 2 + (z & 1)][z >> 1];
                        p = pack2(d[(pr - 1) & 1][2 * z], d[(pr - 1) & 1][2 * z + 1]);
                        asm volatile("" : "+r"(p) :: "memory");
                    }
                }
            }
        }
    }
    if (tid128() == 0) DBG_STAMP(18);
    {
        bf2 vr[2][16], vi[2][16];
        #pragma unroll
        for (int r = 0; r < 16; r++) { vr[0][r] = asbf2(P[r][0]); vr[1][r] = asbf2(P[r][1]); vi[0][r] = asbf2(P[r][2]); vi[1][r] = asbf2(P[r][3]); }
        #pragma unroll
        for (int hb = 0; hb < 2; hb++) {
            const int tid = tid128(), sh = w_first(unit, hb) & 15;
            const uint32_t br = sbase + WBUF(2 * hb), bi = sbase + WBUF(2 * hb + 1);
            const uint32_t pt = lds32(sbase + PT_OFF + 512 * hb + 4 * tid), sp = lds32(sbase + DSK_OFF + 4 * (tid & 31));
            mbar_wait(WQ(hb), 0);
            if ((sh & 1) + 2 * (tid & 7) + 2 <= sh) { const uint32_t a = (tid >> 3) * 1024 + ((sh & 1) + 2 * (tid & 7)) * 2; sts16(br + a, pt); sts16(bi + a, pt >> 16); }
            bar_sync_n(FBAR, 128);
            if (!(unit & 1) && (tid >> 4) == hb) {
                const uint32_t a = w_off(sh + 510 * hb) + (tid & 15) * 1024;
                sts16(br + a, sp); sts16(bi + a, sp >> 16);
            }
            __syncwarp();
            boundary();
            #pragma unroll
            for (int r = 0; r < 16; r++) { pin(vr[0][r]); pin(vi[0][r]); if (!hb) { pin(vr[1][r]); pin(vi[1][r]); } }
            const int pos = 128 * (tid & 3) + 2 * (tid >> 2);
            const bool rot = hb && unit >= 2;
            const uint32_t o0 = w_off(sh + (hb ? 510 - pos : pos)) - (rot ? 1024 : 0), o1 = w_off(sh + (hb ? 446 - pos : pos + 64)) - (rot ? 1024 : 0), oz = rot ? 16384 : 0;
            uint32_t wr[16], wi[16];
            wr[0] = lds_w<0>(br + o0 + oz, br + o1 + oz);
            load_ws<1>(wr, br + o0, br + o1);
            if (hb == 0) {
                dft16(vr[0], vi[0]);
                if (unit > 999) sts32(sbase + SACT_OFF + 4, wr[15]);
                bar_arrive_n(LBAR + 2, 160);
                boundary();
                #pragma unroll
                for (int r = 0; r < 16; r++) { pin(vr[1][r]); pin(vi[1][r]); }
            }
            wi[0] = lds_w<0>(bi + o0 + oz, bi + o1 + oz);
            load_ws<1>(wi, bi + o0, bi + o1);
            if (hb == 0) dft16(vr[1], vi[1]); else idft16(vr[0], vi[0]);
            #pragma unroll
            for (int s = 0; s < 16; s++) cmul2(vr[hb][s], vi[hb][s], asbf2(wr[s]), asbf2(wi[s]));
        }
        bar_sync_n(FBAR, 128);
        idft16(vr[1], vi[1]);
        #pragma unroll
        for (int r = 0; r < 16; r++) { P[r][0] = asu32(vr[0][r]); P[r][1] = asu32(vr[1][r]); P[r][2] = asu32(vi[0][r]); P[r][3] = asu32(vi[1][r]); }
    }
    if (tid128() == 0) DBG_STAMP(19);
    {
        const int tid = tid128();
        const uint4 t = __ldg(reinterpret_cast<const uint4*>(tb->tw[1][tid]));
        const uint32_t zero = unit >> 8;
        const uint32_t sa = sbase + R1 + ((tid >> 3) & 1) * 1024 + (2 * (tid >> 5) + ((tid >> 4) & 1)) * 128 + (tid & 7) * 16;
        float acc[2][16];
        #pragma unroll
        for (int pr = 0; pr < 9; pr++) {
            if (BND && (pr % BND) == 0) boundary();
            if (pr < 8) {
                uint32_t a[8];
                #pragma unroll
                for (int z = 0; z < 8; z++) asm volatile("xor.b32 %0, %1, %2;" : "=r"(a[z]) : "r"(P[2 * pr + (z >> 2)][z & 3]), "r"(zero) : "memory");
                wgmma_fence();
                rs32_z(acc[pr & 1], a[0], a[4], a[1], a[5], mkd(s16, R2 + 8192, 128, 512));
                rs32(acc[pr & 1], a[2], a[6], a[3], a[7], mkd(s16, R2 + 8192 + 256, 128, 512));
                wgmma_commit();
            }
            if (pr > 0) {
                if (pr < 8) wgmma_wait<1>(); else wgmma_wait<0>();
                reg_fence<16>(acc[(pr - 1) & 1]);
                #pragma unroll
                for (int rl = 0; rl < 2; rl++) {
                    const float* a = acc[(pr - 1) & 1] + 2 * rl;
                    bf2 r0 = asbf2(pack2(a[0], a[1])), r1 = asbf2(pack2(a[4], a[5])), i0 = asbf2(pack2(a[8], a[9])), i1 = asbf2(pack2(a[12], a[13]));
                    cmul2(r0, i0, asbf2(t.x), asbf2(t.y)); cmul2(r1, i1, asbf2(t.z), asbf2(t.w));
                    stsm_x4(sa + (2 * pr - 2 + rl) * 2048, asu32(r0), asu32(r1), asu32(i0), asu32(i1));
                }
            }
        }
    }
    fence_async();
    bar_sync_n(FBAR, 128);
    if (tid128() == 0) DBG_STAMP(20);
    {
        const int tid = tid128(), ka = unit >> 1;
        uint8_t* dst = reinterpret_cast<uint8_t*>(g_X2) + (2 * (tid >> 5)) * X2_IMG + (unit & 1) * (X2_IMG / 2)
                     + (16 * (ka >> 3) + 8 * ((tid >> 4) & 1) + (ka & 7)) * 128 + ((((tid >> 1) & 7) ^ (ka & 7)) << 4) + (tid & 1) * 8;
        float acc[64];
        uint32_t o[32], tp = 0;
        #pragma unroll
        for (int h = 0; h < 3; h++) {
            if (h < 2) {
                wgmma_fence();
                ss128_z<0, 1>(acc, mkd(s16, R2, 128, 1024), mkd(s16, R1 + h * 16384, 128, 1024));
                #pragma unroll
                for (int s = 1; s < 4; s++) ss128<0, 1>(acc, mkd(s16, R2 + s * 256, 128, 1024), mkd(s16, R1 + h * 16384 + s * 256, 128, 1024));
                wgmma_commit();
            }
            if (h > 0) {
                yield_to_scan(sbase);
                if (h == 1 || (int)(clk32() - tp) > PC2) tp = clk32() + (tid >> 5) * (PC2 / 2);
                #pragma unroll
                for (int z = 0; z < 16; z++) { if (!(z & 1)) pace(tp, 2 * PC2); __stcg(reinterpret_cast<uint2*>(dst + (64 * h - 64 + 8 * (z >> 1) + (z & 1)) * X2_IMG), make_uint2(o[2 * z], o[2 * z + 1])); }
            }
            if (h < 2) {
                wgmma_wait<0>();
                reg_fence<64>(acc);
                #pragma unroll
                for (int z = 0; z < 16; z++) { const float* a = acc + 8 * (z >> 1) + 2 * (z & 1); o[2 * z] = pack2(a[0], a[1]); o[2 * z + 1] = pack2(a[4], a[5]); asm volatile("" : "+r"(o[2 * z]), "+r"(o[2 * z + 1]) :: "memory"); }
                boundary();
            }
        }
    }
}

struct Maps { CUtensorMap Bre, Bim, X, Xr, Cre, Cim, W[2]; };
#define PSL 100
#define MAPV 0
#define SP1 0
#define SP2 2
#define GBAR 10
#define KBAR 11
#define HOLD 15
#define EAGG 8
#define YP1 1
#define PCR 96
#define PCG 0
#define YIELD 1u
#define ZOK (bars + 80)
#define TBAR 4
#define STAG 2
#define TTAB 8500
#define W0E 0
#define DBGS 3
#define SHP 1
#define REL2 1
#define SBV 1
#define TST 0
#define PD0 20
#define PFC 12000
#define PFCS 2000
#define PFX 6
#define PFW 5000
#define PFB 9000

#define SBASE 0x400u
template <int S> __device__ __forceinline__ void release(uint32_t rel, uint32_t bars) {
    if (REL2) mbar_arrive(EMPTY(S));
    asm volatile("mbarrier.arrive.shared::cluster.b64 _, [%0 + %1];" :: "r"(rel), "n"(8 * (RING + S)) : "memory");
}
__device__ __forceinline__ int peer_role(uint32_t a) { int v; asm volatile("ld.shared::cluster.u32 %0, [%1];" : "=r"(v) : "r"(a ^ (1u << 24)) : "memory"); return v; }
__device__ __forceinline__ void tma_load_2d_mc(uint32_t dst, const CUtensorMap* map, int c0, int c1, uint32_t bar) {
    asm volatile("cp.async.bulk.tensor.2d.shared::cluster.global.mbarrier::complete_tx::bytes.multicast::cluster [%0], [%1, {%3, %4}], [%2], %5;"
        :: "r"(dst), "l"(map), "r"(bar), "r"(c0), "r"(c1), "h"((unsigned short)3) : "memory");
}
__device__ __forceinline__ void bulk_load_mc(uint32_t dst, const void* src, uint32_t bytes, uint32_t bar) {
    asm volatile("cp.async.bulk.shared::cluster.global.mbarrier::complete_tx::bytes.multicast::cluster [%0], [%1], %2, [%3], %4;"
        :: "r"(dst), "l"(src), "r"(bytes), "r"(bar), "h"((unsigned short)3) : "memory");
}
template <int TA> __device__ __forceinline__ void mma_round(float* acc, uint32_t bars, uint32_t a16, uint32_t ph, bool lead, int accum, int it, uint32_t& nw, uint32_t peer, bool lag = false) {
    #pragma unroll
    for (int s = 0; s < RING; s++) {
        if (TA && STAG && s == STAG - 1 && lag) bar_sync_n(TBAR, 256);
        if (TA && STAG && s == STAG && lag) bar_sync_n(TBAR + 1, 256);
        mbar_wait_n(FULL(s), ph, nw);
        wgmma_fence();
        #pragma unroll
        for (int k = 0; k < 4; k++) {
            const uint64_t da = TA ? mkd(a16, s * STGB + k * 256, 128, 1024) : mkd(a16, s * STGB + k * 32, 16, 1024, 1);
            const uint64_t db = mkd(SBASE / 16, s * STGB + 16384 + k * 32, 16, 1024, 1);
            if (k == 0 && s == 0) ss128_p<TA, 0>(acc, da, db, accum); else ss128<TA, 0>(acc, da, db);
        }
        wgmma_commit();
        wgmma_wait<1>();
        if ((s == 3 || s == DBGS) && threadIdx.x == 0) DBG_STAMP(32 + it + s);
        if (lead && (s > 0 ? (!TA || accum < 7) : accum)) { if (s == 0) release<3>(peer, bars); if (s == 1) release<0>(peer, bars); if (s == 2) release<1>(peer, bars); if (s == 3) release<2>(peer, bars); }
    }
}
__device__ __forceinline__ void gemm_main(float* A, uint32_t sbase, int wg, int warp, int lane) {
    const uint32_t bars = sbase + BAR_OFF;
    const bool lead = tid128() < 2 - REL2;
    const uint32_t a16 = SBASE / 16 + wg * 512;
    uint32_t nw = 0;
    uint32_t peer = bars ^ ((uint32_t)(lane + REL2) << 24);
    asm volatile("" : "+r"(peer));
    asm volatile("barrier.cluster.wait.acquire.aligned;" ::: "memory");
    #pragma unroll 1
    for (int half = 0; half < 2; half++) {
        #pragma unroll 1
        for (int rd = 0; rd < 4; rd++) mma_round<0>(A, bars, a16, rd & 1, lead, rd, 16 * half + 4 * rd, nw, peer);
        mbar_wait_n(R0F, half, nw);
        const uint32_t a = sbase + R0 + wg * 16384 + (lane & 3) * 2048 + (((16 * warp + (lane >> 2)) ^ (2 * (lane & 3))) << 4);
        wgmma_wait<0>();
        reg_fence<64>(A);
        if (lead) release<RING - 1>(peer, bars);
        #pragma unroll
        for (int c = 0; c < 8; c++) {
            const float* u = A + c;
            sts128(a + (c >> 2) * 8192 + (c & 1) * 1024 + ((c >> 1) & 1) * 128, pack2(u[0], u[8]), pack2(u[16], u[24]), pack2(u[32], u[40]), pack2(u[48], u[56]));
        }
        bar_arrive_n(DBAR, 384);
        if (threadIdx.x == 0) DBG_STAMP(1 + half);
        if (HOLD >= 0) bar_sync_n(KBAR, 384);
    }
    #pragma unroll 1
    for (int rd = 0; rd < 8; rd++) mma_round<1>(A, bars, a16, rd & 1, lead, rd, 32 + 4 * rd, nw, peer, rd * wg == 7);
}

__device__ __forceinline__ const CUtensorMap* keep(const CUtensorMap* p) { return reinterpret_cast<const CUtensorMap*>(__shfl_sync(0xffffffffu, reinterpret_cast<unsigned long long>(p), 0)); }
__device__ __forceinline__ void produce(const Maps& mp, uint32_t sbase, int RK, int cb, int tc, int db, int rc) {
    const uint32_t bars = sbase + BAR_OFF;
    const CUtensorMap *mr = keep(&mp.Bre), *mi = keep(&mp.Bim), *mx = keep(&mp.X), *cr = keep(&mp.Cre), *ci = keep(&mp.Cim);
    if (!elect_one()) return;
    uint32_t nw = 0;
    int kc = 256, row = cb * 128;
    const int xrow = tc * 128 + RK * 64;
    #pragma unroll 1
    for (int rd = 1; rd < 8; rd++) {
        #pragma unroll
        for (int s = 0; s < RING; s++) {
            mbar_wait_n(EMPTY(s), (rd - 1) & 1, nw);
            mbar_expect_tx(FULL(s), STGB);
            tma_load_2d(sbase + s * STGB, mr, kc, row, FULL(s));
            tma_load_2d(sbase + s * STGB + 8192, mi, kc, row, FULL(s));
            tma_load_2d_mc(sbase + s * STGB + 16384 + RK * 8192, mx, kc, xrow, FULL(s));
            asm volatile("add.s32 %0, %0, 64;" : "+r"(kc));
        }
        if (rd == 3) { kc = 0; row += 64; }
    }
    const uint8_t* hs = reinterpret_cast<const uint8_t*>(g_h) + rc * 32 * 16384 + RK * 8192;
    const int d0 = db * 4, d1 = db * 4 + 32;
    #pragma unroll 1
    for (int rd = 8; rd < 16; rd++) {
        const CUtensorMap* cm = (rd & 2) ? ci : cr;
        kc = (rd & 1) * 512 + (rd & 4) * 16;
        #pragma unroll
        for (int s = 0; s < RING; s++) {
            mbar_wait_n(EMPTY(s), (rd - 1) & 1, nw);
            mbar_expect_tx(FULL(s), STGB);
            tma_load_5d(sbase + s * STGB + 16384, cm, kc, d0, FULL(s));
            tma_load_5d(sbase + s * STGB + 24576, cm, kc, d1, FULL(s));
            if (s == 0) { mbar_wait_n(HOK((rd >> 1) & 3), 0, nw); if (!(rd & 3)) DBG_STAMP(13 + ((rd >> 2) & 1)); }
            bulk_load_mc(sbase + s * STGB + RK * 8192, hs, 8192, FULL(s));
            asm volatile("add.s32 %0, %0, 128;" : "+r"(kc));
            asm volatile("add.s64 %0, %0, 16384;" : "+l"(hs));
        }
    }
}

__global__ void __cluster_dims__(2, 1, 1) __launch_bounds__(640, 1)
fused_kernel(const __grid_constant__ Maps mp, const __nv_bfloat16* __restrict__ x,
             const __nv_bfloat16* __restrict__ w_r, const __nv_bfloat16* __restrict__ w_i,
             const __nv_bfloat16* __restrict__ lam_re, const __nv_bfloat16* __restrict__ lam_im,
             const __nv_bfloat16* __restrict__ log_dt, const __nv_bfloat16* __restrict__ dskip,
             const __nv_bfloat16* __restrict__ gate_w,
             const __nv_bfloat16* __restrict__ Cre, const __nv_bfloat16* __restrict__ Cim,
             const __nv_bfloat16* __restrict__ Bre, const __nv_bfloat16* __restrict__ Bim, float* __restrict__ out, unsigned int full) {
    extern __shared__ __align__(1024) uint8_t smem[];
    const uint32_t sbase = SBASE + ((blockIdx.x & 1) << 24);
    if (smem_u32(smem) != sbase) __trap();
    const uint32_t bars = sbase + BAR_OFF;
    const int tid = threadIdx.x, lane = tid & 31;
    const int wg = __shfl_sync(0xffffffffu, tid >> 7, 0), warp = __shfl_sync(0xffffffffu, (tid >> 5) & 3, 0);
    int cta = blockIdx.x;
    {
        unsigned int smid, nsm;
        asm volatile("mov.u32 %0, %%smid;" : "=r"(smid));
        asm volatile("mov.u32 %0, %%nsmid;" : "=r"(nsm));
        if (nsm == full) {
            const int t = smid >> 1, u = (t - 32) / 7;
            const int g = t < 32 ? (t & 7) : (t < 60 ? t - 31 - 7 * u : 0), idx = t < 32 ? (t >> 3) : (t < 60 ? 4 + u : t - 58);
            const int lg = (0x73216540 >> (4 * g)) & 7;
            cta = ((t & ~1) == 60 ? 8 + 2 * t : 16 * lg + 2 * idx) + (TST & 1 ? (blockIdx.x & 1) : (smid & 1));
        }
    }
    const int cb = 2 * (cta >> 5) + (cta & 1), tc = (cta >> 1) & 15;
    const int db = 2 * ((cta >> 4) & 3) + (cta & 1), rc = 8 * ((cta >> 6) & 1) + ((cta >> 1) & 7);
    const long long t_start = clock64();
    if (tid >= 512 && tid < 544 && elect_one()) {
        DBG_STAMP(0); DBG_RAW(98, (cta + 1) * 1000);
        for (int s = 0; s < RING; s++) { mbar_init(FULL(s), 1); mbar_init(EMPTY(s), 4); }
        for (int i = 0; i < 12; i++) mbar_init(XB + 8 * i, i >= 10 || i == 4 ? 2 : (i == 2 ? 129 : 1));
        mbar_init(X1C, 1);
        sts32(sbase + ROLE_OFF, cta); sts32(sbase + SACT_OFF, 0u); sts32(sbase + SACT_OFF + 8, 0u);
        asm volatile("fence.mbarrier_init.release.cluster;" ::: "memory");
        fence_async();
        if (cta < 128) {
            #pragma unroll
            for (int s = 0; s < RING; s++) {
                mbar_expect_tx(FULL(s), STGB);
                tma_load_2d(sbase + s * STGB, &mp.Bre, s * 64, cb * 128, FULL(s));
                tma_load_2d(sbase + s * STGB + 8192, &mp.Bim, s * 64, cb * 128, FULL(s));
                tma_load_2d(sbase + s * STGB + 16384, &mp.X, s * 64, tc * 128, FULL(s));
                tma_load_2d(sbase + s * STGB + 24576, &mp.X, s * 64, tc * 128 + 64, FULL(s));
            }
        }
    }
    __syncthreads();
    asm volatile("barrier.cluster.arrive.relaxed.aligned;" ::: "memory");
    if (wg >= 2 || cta >= 128) asm volatile("barrier.cluster.wait.acquire.aligned;" ::: "memory");
    if (wg == 4) {
        asm volatile("setmaxnreg.dec.sync.aligned.u32 24;");
        if (warp == 0) {
            const int prole = (TST & 4) ? (cta ^ 1) : __shfl_sync(0xffffffffu, peer_role(sbase + ROLE_OFF), 0);
            const uint32_t rk = blockIdx.x & 1;
            if (cta >= 128) bar_arrive_n(DBAR + (prole >> 30), 64);
            const uint8_t* hs = reinterpret_cast<const uint8_t*>(g_h) + rc * 32 * 16384;
            if (cta < 128 && __all_sync(0xffffffffu, prole == (cta ^ 1))) {
                produce(mp, sbase, rk, cb, tc, db, rc);
            } else if (cta < 128) {
                uint32_t nw = 0;
                if (elect_one()) {
                    #pragma unroll 1
                    for (int it = RING; it < 64; it++) {
                        const int s = it % RING;
                        const uint32_t sa = sbase + s * STGB;
                        if (prole >= 128) mbar_arrive2(EMPTY(s));
                        mbar_wait_n(EMPTY(s), ((it / RING) - 1) & 1, nw);
                        mbar_expect_tx(FULL(s), STGB);
                        if (it < 32) {
                            tma_load_2d(sa, &mp.Bre, (it & 15) * 64, cb * 128 + (it >> 4) * 64, FULL(s));
                            tma_load_2d(sa + 8192, &mp.Bim, (it & 15) * 64, cb * 128 + (it >> 4) * 64, FULL(s));
                            tma_load_2d(sa + 16384, &mp.X, (it & 15) * 64, tc * 128, FULL(s));
                            tma_load_2d(sa + 24576, &mp.X, (it & 15) * 64, tc * 128 + 64, FULL(s));
                        } else {
                            const CUtensorMap* cm = (it & 8) ? &mp.Cim : &mp.Cre;
                            tma_load_5d(sa + 16384, cm, (it & 7) * 128 + (it & 16) * 4, db * 4, FULL(s));
                            tma_load_5d(sa + 24576, cm, (it & 7) * 128 + (it & 16) * 4, db * 4 + 32, FULL(s));
                            mbar_wait_n(HOK((it >> 3) & 3), 0, nw);
                            bulk_load(sa, hs + (it - 32) * 16384, 16384, FULL(s));
                        }
                    }
                }
            } else if (cta >= 128 && prole < 128 && lane == 0) {
                mbar_arrive2(EMPTY(RING - 1));
                #pragma unroll 1
                for (int p = 0; p < 8; p++) mbar_wait(EMPTY(RING - 1), p & 1);
            }
        } else if (warp == 1) {
            if (cta < 130) {
                #pragma unroll 1
                for (int i = lane; i < 128; i += 32) {
                    const int p = (cb & 7) * 128 + i;
                    const float dt = bf16r(expf(__bfloat162float(log_dt[p]))), lr = __bfloat162float(lam_re[p]), li = __bfloat162float(lam_im[p]);
                    const float er = expf(dt * lr), den = lr * lr + li * li;
                    float sn, cs; sincospif(dt * li * 0.31830988618379067154f, &sn, &cs);
                    cs *= er; sn *= er;
                    sts128(sbase + LAM_OFF + i * 16, __float_as_uint(cs), __float_as_uint(sn),
                           __float_as_uint(__fdividef((cs - 1.f) * lr + sn * li, den)), __float_as_uint(__fdividef(sn * lr - (cs - 1.f) * li, den)));
                }
                __syncwarp();
                if (lane == 0) mbar_arrive(EPB);
                mbar_wait(EPB, 0);
                const unsigned int epoch = lds32(sbase + EPO_OFF);
                const bool one = elect_one();
                if (one) {
                    while (clock64() - t_start < TTAB) { __nanosleep(100); }
                    mbar_expect_tx(X1B, 16384 + 2048 + 10240);
                    bulk_load(sbase + B16F_OFF, g_img.b16f, 2048, X1B);
                    bulk_load(sbase + R2, cta < 2 ? g_img.m4re[cta] : g_img.h[cta & 1].m4, 8192, X1B);
                    bulk_load(sbase + R2 + 8192, g_img.h[cta & 1].b16i, 2048, X1B);
                    if (W0E) { delay(300); load_w(mp.W, sbase, cta, 0); }
                }
                __syncwarp();
                if (cta < 128) bar_sync_n(GBAR, 288);
                if (one) {
                    if (cta < 128) { mbar_arrive(R0F); red_release(&g_cnt1); DBG_STAMP(15); }
                    mbar_expect_tx(X1C, 16384);
                    wait_counter(&g_cnt1, 128u * epoch);
                    DBG_STAMP(8);
                    load_paced(sbase + R1, (ABL & 2) ? reinterpret_cast<const uint8_t*>(x) + (cta & 127) * 32768 : reinterpret_cast<const uint8_t*>(g_X1 + (cta & 127) * 2048), 16384 / PSZ, X1B);
                    load_paced(sbase + R1 + 16384, (ABL & 2) ? reinterpret_cast<const uint8_t*>(x) + (cta & 127) * 32768 + 16384 : reinterpret_cast<const uint8_t*>(g_X1 + (cta & 127) * 2048 + 1024), 16384 / PSZ, X1C);
                }
                #pragma unroll 1
                for (int i = 0; i < 4; i++) {
                    if (one && (i || !W0E)) load_w(mp.W, sbase, cta, i);
                    __syncwarp();
                    bar_sync_n(LBAR + i, 160);
                }
                if (one) {
                    red_release(cta < 128 ? &g_cnt2 : &g_cnt3);
                    DBG_STAMP(30);
                    if (cta < 128) {
                        const uint8_t* img = (ABL & 2) ? reinterpret_cast<const uint8_t*>(x) + (cta & 63) * 65536 : reinterpret_cast<const uint8_t*>(g_X2) + (8 * rc + db) * X2_IMG;
                        mbar_expect_tx(ZOK, 32768 - 256);
                        wait_counter(&g_cnt2, 128u * epoch);
                        DBG_STAMP(31);
                        bulk_load(sbase + R1 + 1152, img + 1152, 15232, ZOK);
                        bulk_load(sbase + R1 + 16384 + 1152, img + X2_IMG / 2 + 1152, 15232, ZOK);
                        bulk_load(sbase + R1, img, 1024, ZOK);
                        bulk_load(sbase + R1 + 16384, img + X2_IMG / 2, 1024, ZOK);
                    }
                }
            }
        } else if (warp == 2) {
            if (cta < 128) {
                const uint8_t* xp = reinterpret_cast<const uint8_t*>(x) + (cta * 16 + (lane & 15)) * 2048 + (lane >> 4) * 128;
                const uint8_t* bp = reinterpret_cast<const uint8_t*>((lane & 16) ? Bim : Bre) + (cb * 128 + tc * 4 + ((lane >> 2) & 3)) * 2048 + (lane & 3) * 128;
                #pragma unroll 1
                for (int k = 4; k < 16; k++) {
                    if (k == PFX && lane == 0) {
                        mbar_expect_tx(XB, 32768);
                        #pragma unroll 1
                        for (int i = 0; i < 8; i++) tma_load_2d(sbase + R0 + i * 4096, &mp.Xr, rc * 1024 + db * 64 + (i >> 2) * 512, (i & 3) * 32, XB);
                    }
                    __syncwarp();
                    if ((k & 3) == 0) pf_line(bp + k * 128);
                    if (!(k & 1)) pf_line(xp + k * 128);
                }
                if ((cta & 63) < 8) pf_line(reinterpret_cast<const uint8_t*>(&g_img) + (cta & 63) * 4096 + lane * 128);
                while (clock64() - t_start < PFW) { }
                const uint32_t wrow = (((cta & 1) ? 128 - (cta >> 1) : (cta >> 1)) + 128 * (lane >> 1)) & 2047;
                const uint8_t* wp = reinterpret_cast<const uint8_t*>(lane & 1 ? w_i : w_r) + wrow * 1026u;

                #pragma unroll 1
                for (int k = 0; k < ((ABL & 4) ? 0 : 9); k++) { pf_line(wp + (k < 8 ? k * 128 : 1024)); __nanosleep(200); }
                while (clock64() - t_start < PFB) { }
                #pragma unroll 1
                for (int k = 0; k < 16; k += 4) { pf_line(bp + 64 * 2048 + k * 128); __nanosleep(200); }
                const uint8_t* cp = reinterpret_cast<const uint8_t*>((lane & 16) ? Cim : Cre) + (cta * 8 + (lane & 7)) * 2048 + (lane & 8) * 32;
                #pragma unroll 1
                for (int k = 0; k < 8; k++) {
                    while (clock64() - t_start < PFC + k * PFCS) { __nanosleep(100); }
                    pf_line(cp + (k & 3) * 512 + (k >> 2) * 128);
                }
            }
        } else {
            unsigned int epoch = 0;
            if (cta >= 128) bar_sync_n(DBAR, 64);
            if (lane == 0) {
                epoch = atomicAdd(&g_ticket, 1u);
                epoch = (full ? epoch / NCTA : epoch / 130u) + 1u;
                sts32(sbase + EPO_OFF, epoch);
                mbar_arrive(EPB);
            }
            __syncwarp();
            if (cta < 128) {
                #pragma unroll 1
                for (int i = 0; i < 4; i++) {
                    bar_sync_n(HBAR + i, 160);
                    if (lane == 0) {
                        red_release(&g_cnth(i));
                        if (!(i & 1)) DBG_STAMP(4 + (i >> 1));
                        wait_counter(&g_cnth(i), 128u * epoch);
                        mbar_arrive(HOK(i));
                    }
                    __syncwarp();
                }
                if (lane == 0) {
                    mbar_expect_tx(XB, 32768);
                    #pragma unroll 1
                    for (int i = 0; i < 8; i++) { tma_load_2d(sbase + R0 + i * 4096, &mp.Xr, rc * 1024 + db * 64 + (i >> 2) * 512, (i & 3) * 32, XB); __nanosleep(150); }
                }
            } else if (cta >= 130 && lane == 0) {
                #pragma unroll 1
                for (int i = 0; i < (1 << 22); i++) {
                    __nanosleep(200);
                    if ((int)(*reinterpret_cast<volatile unsigned int*>(&g_ticket) - NCTA * epoch) >= 0) break;
                }
            }
        }
    } else if (wg >= 2) {
      if (cta < 128) {
          const uint4 gl = __ldg(reinterpret_cast<const uint4*>(gate_w) + db * 8 + (wg - 2) * 64 + (lane & 7));
          gen_dft(sbase + R1, tid128(), 16 * tid128() + rc, 4 * wg - 8, 4 * wg - 4, 1.f, 0.5f);
          if (tid128() < 8) { sts128(sbase + GATE_OFF + (wg - 2) * 128 + lane * 16, gl.x, gl.y, gl.z, gl.w); }
          fence_async();
          bar_sync_n(wg, 128);
          mbar_wait(XB, 0);
          if (tid == 256) DBG_STAMP(9);
          fft_p1(sbase, wg - 2, rc, db, (uint32_t)t_start + P1END);
          bar_arrive_n(GBAR, 288);
      }
      if (wg == 3) {
        asm volatile("setmaxnreg.inc.sync.aligned.u32 128;");
        if (cta < 128) {
            if (cta < 128) {
                mbar_wait(EPB, 0);
                #pragma unroll 1
                for (int half = 0; half < 2; half++) {
                    const int t1 = tid128(), ch = t1 >> 1, hf = t1 & 1, p = cb * 128 + half * 64 + ch;
                    const uint4 pm = lds128(sbase + LAM_OFF + (half * 64 + ch) * 16);
                    float2 lam = make_float2(__uint_as_float(pm.x), __uint_as_float(pm.y));
                    float cr = __uint_as_float(pm.z), ci = __uint_as_float(pm.w);
                    float2 l16 = cmul(lam, lam); l16 = cmul(l16, l16); l16 = cmul(l16, l16); l16 = cmul(l16, l16);
                    float2 l64 = cmul(l16, l16); l64 = cmul(l64, l64);
                    const unsigned int par = lds32(sbase + EPO_OFF) & 1u;
                    {
                        uint32_t z = __float_as_uint(cr) ^ __float_as_uint(ci) ^ __float_as_uint(l64.x) ^ __float_as_uint(l64.y);
                        if (z == 0x9e3779b9u) sts32(sbase + SACT_OFF + 4, z);
                    }
                    bar_sync_n(DBAR, 384);
                    if (t1 == 0) DBG_STAMP(21 + 4 * half);
                    uint2 ur[16], ui[16];
                    #pragma unroll
                    for (int r = 0; r < 16; r++) {
                        const uint32_t a = sbase + R0 + r * 1024 + ((ch ^ (r & 6)) << 4) + hf * 8;
                        ur[r] = lds64(a); ui[r] = lds64(a + 16384);
                    }
                    if (HOLD >= 0) { if (cta > 999) sts32(sbase + SACT_OFF + 4, ui[HOLD].y); bar_arrive_n(KBAR, 384); boundary(); }
                    float2 e[4];
                    e[0] = make_float2(bflo(ur[0].x), bflo(ui[0].x)); e[1] = make_float2(bfhi(ur[0].x), bfhi(ui[0].x));
                    e[2] = make_float2(bflo(ur[0].y), bflo(ui[0].y)); e[3] = make_float2(bfhi(ur[0].y), bfhi(ui[0].y));
                    #pragma unroll
                    for (int r = 1; r < 16; r++) {
                        e[0] = cfma(lam, e[0], make_float2(bflo(ur[r].x), bflo(ui[r].x))); e[1] = cfma(lam, e[1], make_float2(bfhi(ur[r].x), bfhi(ui[r].x)));
                        e[2] = cfma(lam, e[2], make_float2(bflo(ur[r].y), bflo(ui[r].y))); e[3] = cfma(lam, e[3], make_float2(bfhi(ur[r].y), bfhi(ui[r].y)));
                        ur[r] = make_uint2(pack2(e[0].x, e[1].x), pack2(e[2].x, e[3].x)); ui[r] = make_uint2(pack2(e[0].y, e[1].y), pack2(e[2].y, e[3].y));
                        if (SP1 && (r % (SP1 ? SP1 : 1)) == 0) { asm volatile("" : "+r"(ur[r].x), "+r"(ur[r].y), "+r"(ui[r].x), "+r"(ui[r].y) :: "memory"); lam.x = __shfl_sync(0xffffffffu, lam.x, lane); }
                    }
                    e[1] = cfma(l16, e[0], e[1]); e[2] = cfma(l16, e[1], e[2]); e[3] = cfma(l16, e[2], e[3]);
                    float2 E0;
                    E0.x = __shfl_xor_sync(0xffffffffu, e[3].x, 1); E0.y = __shfl_xor_sync(0xffffffffu, e[3].y, 1);
                    if (hf && tc < 15) {
                        const float2 ag = cfma(l64, E0, e[3]);
                        const unsigned long long w = (unsigned long long)((__float_as_uint(ag.x) & ~1u) | par) | ((unsigned long long)((__float_as_uint(ag.y) & ~1u) | par) << 32);
                        asm volatile("st.relaxed.gpu.global.u64 [%0], %1;" :: "l"(&g_agg[tc * P_DIM + p]), "l"(w) : "memory");
                    }
                    const uint2* src = reinterpret_cast<const uint2*>(g_agg) + (tc - 1 - hf) * P_DIM + p;
                    const int nv = tc - hf;
                    uint2 v[8];
                    bar_sync_n(SBAR, 128);
                    if (t1 == 0) { mbar_arrive(R0F); DBG_STAMP(22 + 4 * half); }
                    {
                        cr += __uint_as_float(lds32(sbase + SACT_OFF + 8));
                        ci += __uint_as_float(lds32(sbase + SACT_OFF + 8));
                        const bf2 c2 = asbf2(pack2(cr, cr)), n2 = asbf2(pack2(-cr, -cr)), s2 = asbf2(pack2(-ci, -ci));
                        #pragma unroll
                        for (int r = 0; r < 16; r++) {
                            if (r == EAGG) {
                                boundary();
                                #pragma unroll
                                for (int i = 0; i < 8; i++) {
                                    v[i] = make_uint2(par, par);
                                    if (2 * i < nv) asm volatile("ld.relaxed.gpu.global.v2.u32 {%0, %1}, [%2];" : "=r"(v[i].x), "=r"(v[i].y) : "l"(src - i * 2 * P_DIM) : "memory");
                                }
                                #pragma unroll
                                for (int q = r; q < 16; q++) asm volatile("" : "+r"(ur[q].x), "+r"(ur[q].y), "+r"(ui[q].x), "+r"(ui[q].y) :: "memory");
                            }
                            const bf2 a = asbf2(ur[r].x), b = asbf2(ui[r].x), c = asbf2(ur[r].y), d = asbf2(ui[r].y);
                            ur[r].x = asu32(__hfma2(c2, a, __hmul2(s2, b))); ui[r].x = asu32(__hfma2(n2, b, __hmul2(s2, a)));
                            ur[r].y = asu32(__hfma2(c2, c, __hmul2(s2, d))); ui[r].y = asu32(__hfma2(n2, d, __hmul2(s2, c)));
                            if (r < EAGG) asm volatile("" : "+r"(ur[r].x), "+r"(ur[r].y), "+r"(ui[r].x), "+r"(ui[r].y) :: "memory");
                        }
                    }
                    const float2 l32 = cmul(l16, l16), l128 = cmul(l64, l64), l256 = cmul(l128, l128);
                    #pragma unroll 1
                    for (int spins = 0; spins < (1 << 20); spins++) {
                        uint32_t bad = 0;
                        #pragma unroll
                        for (int i = 0; i < 8; i++) bad |= (v[i].x ^ par) | (v[i].y ^ par);
                        if (!__any_sync(0xffffffffu, bad & 1u)) break;
                        #pragma unroll
                        for (int i = 0; i < 8; i++)
                            if (2 * i < nv) asm volatile("ld.relaxed.gpu.global.v2.u32 {%0, %1}, [%2];" : "+r"(v[i].x), "+r"(v[i].y) : "l"(src - i * 2 * P_DIM) : "memory");
                    }
                    if (t1 == 0) { sts32(sbase + SACT_OFF, YIELD); DBG_STAMP(23 + 4 * half); }
                    float2 H = make_float2(__uint_as_float(v[7].x), __uint_as_float(v[7].y));
                    #pragma unroll
                    for (int i = 6; i >= 0; i--) H = cfma(l256, H, make_float2(__uint_as_float(v[i].x), __uint_as_float(v[i].y)));
                    if (hf) H = cmul(H, l128);
                    H.x += __shfl_xor_sync(0xffffffffu, H.x, 1); H.y += __shfl_xor_sync(0xffffffffu, H.y, 1);
                    float2 st[4];
                    st[0] = hf ? cfma(l64, H, E0) : H;
                    st[1] = cfma(l16, st[0], e[0]); st[2] = cfma(l32, st[0], e[1]); st[3] = cfma(l16, cmul(l32, st[0]), e[2]);
                    const bf2 gr0 = asbf2(pack2(cr * st[0].x - ci * st[0].y, cr * st[1].x - ci * st[1].y)), gr1 = asbf2(pack2(cr * st[2].x - ci * st[2].y, cr * st[3].x - ci * st[3].y));
                    const bf2 gi0 = asbf2(pack2(-ci * st[0].x - cr * st[0].y, -ci * st[1].x - cr * st[1].y)), gi1 = asbf2(pack2(-ci * st[2].x - cr * st[2].y, -ci * st[3].x - cr * st[3].y));
                    uint2* dst = reinterpret_cast<uint2*>(g_h + (half * 16 + cb) * 1024 + tc * 64) + t1;
                    lam.y = -lam.y;
                    float2 z = lam;
                    uint32_t pw[16], tp = clk32() + warp * (PCH / 2);
                    #pragma unroll
                    for (int r = 0; r < 16; r++) {
                        pw[r] = pack2(z.x, z.y); z = cmul(z, lam);
                        const bf2 pr = __low2bfloat162(asbf2(pw[r])), pi = __high2bfloat162(asbf2(pw[r]));
                        if (!(r & 1)) pace(tp, 2 * PCR);
                        __stcg(dst + r * 65536, make_uint2(asu32(__hfma2(pr, gr0, __hfma2(pi, neg2(gi0), asbf2(ur[r].x)))), asu32(__hfma2(pr, gr1, __hfma2(pi, neg2(gi1), asbf2(ur[r].y))))));
                    }
                    bar_arrive_n(HBAR + 2 * half, 160);
                    if (t1 == 0) DBG_STAMP(24 + 4 * half);
                    if (PCR == 0) tp = clk32();
                    tp += PCG;
                    #pragma unroll
                    for (int r = 0; r < 16; r++) {
                        const bf2 pr = __low2bfloat162(asbf2(pw[r])), pi = __high2bfloat162(asbf2(pw[r]));
                        if (!(r & 1)) pace(tp, 2 * PCH);
                        __stcg(dst + r * 65536 + 16384, make_uint2(asu32(__hfma2(pr, gi0, __hfma2(pi, gr0, asbf2(ui[r].x)))), asu32(__hfma2(pr, gi1, __hfma2(pi, gr1, asbf2(ui[r].y))))));
                    }
                    bar_arrive_n(HBAR + 2 * half + 1, 160);
                    if (t1 == 0) sts32(sbase + SACT_OFF, 0u);
                }
            }
        }
      } else {
        asm volatile("setmaxnreg.inc.sync.aligned.u32 136;");
        if (cta < 130) {
            if (tid128() == 0) DBG_STAMP(16);
            fft_p2(sbase, bars, cta, w_r, w_i);
            bar_sync_n(LBAR + 3, 160);
            if (tid128() == 0) DBG_STAMP(29);
            if (cta < 128) {
                const int j = tid128();
                if (j < 16) {
                    const uint2 d0 = __ldg(reinterpret_cast<const uint2*>(dskip) + db * 16 + j), d1 = __ldg(reinterpret_cast<const uint2*>(dskip) + db * 16 + 128 + j);
                    sts128(sbase + DSK_OFF + j * 16, d0.x, d0.y, d1.x, d1.y);
                }
                float s = 0.f;
                #pragma unroll
                for (int i = 0; i < 16; i++) s += __ldcg(&g_gp[(16 * rc + i) * 128 + j]);
                const float gv = bf16r(__fdividef(1.f, 1.f + expf(-bf16r(s))));
                sts32(sbase + GATE_OFF + 4 * j, __float_as_uint(bf16r(1.f - gv)));
                gen_dft(sbase + R2, j, 16 * j + rc, 0, 8, gv * (1.f / 1048576.f), gv * (1.f / 1048576.f));
                const uint8_t* img = reinterpret_cast<const uint8_t*>(g_X2) + (8 * rc + db) * X2_IMG;
                if ((j >> 4) == 4) {
                    wait_counter(&g_cnt3, 2u * lds32(sbase + EPO_OFF));
                    const float cs = g_img.cs[0][4 * rc][0], sn = g_img.cs[0][4 * rc][1];
                    const uint4* s4 = reinterpret_cast<const uint4*>(img + ((j >> 3) & 1) * (X2_IMG / 2) + 16384) + (j & 7);
                    const uint4 a = __ldcg(s4), b = __ldcg(s4 + 64);
                    sts128(sbase + R1 + ((j >> 3) & 1) * 16384 + 1024 + (j & 7) * 16,
                           pack2(cs * bflo(a.x) - sn * bflo(b.x), cs * bfhi(a.x) - sn * bfhi(b.x)), pack2(cs * bflo(a.y) - sn * bflo(b.y), cs * bfhi(a.y) - sn * bfhi(b.y)),
                           pack2(cs * bflo(a.z) - sn * bflo(b.z), cs * bfhi(a.z) - sn * bfhi(b.z)), pack2(cs * bflo(a.w) - sn * bflo(b.w), cs * bfhi(a.w) - sn * bfhi(b.w)));
                }
                fence_async();
                mbar_arrive(ZOK);
            }
        }
      }
    } else {
        if (cta < 128) {
            float A[64];
            #pragma unroll
            for (int i = 0; i < 64; i++) A[i] = 0.f;
            gemm_main(A, sbase, wg, warp, lane);
            if (tid == 0) DBG_STAMP(12);
            const int ln = tid128() & 31, row = 64 * wg + 16 * warp + (ln >> 2);
            if (STAG && wg == 0) bar_arrive_n(TBAR, 256);
            mbar_wait(ZOK, 0);
            if (tid == 0) DBG_STAMP(11);
            float om[2];
            om[0] = __uint_as_float(lds32(sbase + GATE_OFF + 4 * row)); om[1] = __uint_as_float(lds32(sbase + GATE_OFF + 4 * row + 32));
            wgmma_wait<0>();
            reg_fence<64>(A);
            #pragma unroll
            for (int i = 0; i < 32; i++) { const float o = om[(i >> 1) & 1], t = o * A[i], u = A[i + 32]; A[i] = fmaf(o, u, t); A[i + 32] = fmaf(-o, u, t); }
            const uint32_t s16 = to16(sbase);
            wgmma_fence();
            #pragma unroll
            for (int ks = 0; ks < 8; ks++)
                ss128<0, 1>(A, mkd(s16 + wg * 512, R2 + (ks >> 2) * 16384 + (ks & 3) * 32, 16, 1024, 1), mkd(s16, R1 + ks * 2048, 16384, 1024, 1));
            wgmma_commit();
            if (STAG && wg == 0) bar_arrive_n(TBAR + 1, 256);
            float* o = out + (size_t)(16 * row + rc) * 1024 + db * 64 + 4 * (ln & 3);
            mbar_wait(XB, 1);
            wgmma_wait<0>();
            reg_fence<64>(A);
            if (tid128() == 0) DBG_STAMP(120 + wg);
            #pragma unroll
            for (int J = 0; J < 4; J++) {
                if (J) boundary();
                const uint4 dk = lds128(sbase + DSK_OFF + (4 * J + (ln & 3)) * 16);
                #pragma unroll
                for (int h = 0; h < 2; h++) {
                    const uint32_t xo = sbase + R0 + (row + 8 * h) * 128 + (ln & 1) * 8 + (((2 * J + ((ln >> 1) & 1)) ^ (ln >> 2)) << 4);
                    uint2 p = lds64(xo), s = lds64(xo + 16384);
                    p.x = hmul2bf(p.x, dk.x); p.y = hmul2bf(p.y, dk.y); s.x = hmul2bf(s.x, dk.z); s.y = hmul2bf(s.y, dk.w);
                    const float* a = A + 8 * J + 2 * h;
                    __stcs(reinterpret_cast<float4*>(o + h * 131072 + J * 16),
                           make_float4(fmaf(om[h], bflo(p.x), a[0] + a[32]), fmaf(om[h], bfhi(p.x), a[1] + a[33]), fmaf(om[h], bflo(p.y), a[4] + a[36]), fmaf(om[h], bfhi(p.y), a[5] + a[37])));
                    __stcs(reinterpret_cast<float4*>(o + h * 131072 + J * 16 + 512),
                           make_float4(fmaf(om[h], bflo(s.x), a[0] - a[32]), fmaf(om[h], bfhi(s.x), a[1] - a[33]), fmaf(om[h], bflo(s.y), a[4] - a[36]), fmaf(om[h], bfhi(s.y), a[5] - a[37])));
                }
            }
            if (tid == 128) { DBG_STAMP(122); DBG_END; }
            if (tid == 0) DBG_STAMP(7);
        }
    }
}

typedef CUresult (*PFN_encodeTiled_t)(CUtensorMap*, CUtensorMapDataType, cuuint32_t, void*, const cuuint64_t*, const cuuint64_t*,
                                      const cuuint32_t*, const cuuint32_t*, CUtensorMapInterleave, CUtensorMapSwizzle,
                                      CUtensorMapL2promotion, CUtensorMapFloatOOBfill);

static void make_map(PFN_encodeTiled_t enc, CUtensorMap* m, int rank, const void* ptr, const cuuint64_t* dims, const cuuint64_t* strides, const cuuint32_t* box) {
    cuuint32_t es[5] = {1, 1, 1, 1, 1};
    enc(m, CU_TENSOR_MAP_DATA_TYPE_BFLOAT16, rank, (void*)ptr, dims, strides, box, es, CU_TENSOR_MAP_INTERLEAVE_NONE, CU_TENSOR_MAP_SWIZZLE_128B,
        CU_TENSOR_MAP_L2_PROMOTION_L2_128B, CU_TENSOR_MAP_FLOAT_OOB_FILL_NONE);
}
static void make_map_2d(PFN_encodeTiled_t enc, CUtensorMap* m, const void* ptr, int rows, int cols, int box_rows) {
    cuuint64_t dims[2] = {(cuuint64_t)cols, (cuuint64_t)rows};
    cuuint64_t strides[1] = {(cuuint64_t)cols * 2};
    cuuint32_t box[2] = {64, (cuuint32_t)box_rows};
    make_map(enc, m, 2, ptr, dims, strides, box);
}

extern "C" void kernel_launch(void* const* d_in, const int* in_sizes, int n_in, void* d_out, int out_size) {
    const __nv_bfloat16* x = (const __nv_bfloat16*)d_in[0];
    const __nv_bfloat16* w_r = (const __nv_bfloat16*)d_in[1];
    const __nv_bfloat16* w_i = (const __nv_bfloat16*)d_in[2];
    const __nv_bfloat16* lam_re = (const __nv_bfloat16*)d_in[4];
    const __nv_bfloat16* lam_im = (const __nv_bfloat16*)d_in[5];
    const __nv_bfloat16* B_re = (const __nv_bfloat16*)d_in[6];
    const __nv_bfloat16* B_im = (const __nv_bfloat16*)d_in[7];
    const __nv_bfloat16* C_re = (const __nv_bfloat16*)d_in[8];
    const __nv_bfloat16* C_im = (const __nv_bfloat16*)d_in[9];
    const __nv_bfloat16* log_dt = (const __nv_bfloat16*)d_in[10];
    const __nv_bfloat16* dskip = (const __nv_bfloat16*)d_in[11];
    const __nv_bfloat16* gate_w = (const __nv_bfloat16*)d_in[12];

    static PFN_encodeTiled_t enc = nullptr;
    static Maps mp;
    static int grid = 130;
    static const void* key[7] = {nullptr, nullptr, nullptr, nullptr, nullptr, nullptr, nullptr};
    if (!enc) {
        cudaDriverEntryPointQueryResult qres;
        cudaGetDriverEntryPoint("cuTensorMapEncodeTiled", (void**)&enc, cudaEnableDefault, &qres);
        cudaFuncSetAttribute(fused_kernel, cudaFuncAttributeMaxDynamicSharedMemorySize, TOT_SMEM);
        int dev = 0, nsm = 0;
        cudaGetDevice(&dev);
        cudaDeviceGetAttribute(&nsm, cudaDevAttrMultiProcessorCount, dev);
        grid = nsm == NCTA ? NCTA : 130;
    }
    if (key[0] != x || key[1] != B_re || key[2] != B_im || key[3] != C_re || key[4] != C_im || key[5] != w_r || key[6] != w_i) {
        make_map_2d(enc, &mp.Bre, B_re, P_DIM, D_DIM, 64);
        make_map_2d(enc, &mp.Bim, B_im, P_DIM, D_DIM, 64);
        make_map_2d(enc, &mp.X, x, S_LEN, D_DIM, 64);
        make_map_2d(enc, &mp.Xr, x, S_LEN / 16, D_DIM * 16, 32);
        {
            cuuint64_t dims[5] = {P_DIM, 2, 4, 2, D_DIM / 16};
            cuuint64_t strides[4] = {P_DIM * 2, P_DIM * 2 * 4, P_DIM * 2 * 2, P_DIM * 2 * 16};
            cuuint32_t box[5] = {64, 2, 4, 2, 4};
            make_map(enc, &mp.Cre, 5, C_re, dims, strides, box);
            make_map(enc, &mp.Cim, 5, C_im, dims, strides, box);
        }
        for (int a = 0; a < 2; a++) {
            cuuint64_t dims[3] = {128 * 513 - 448, 8, 16};
            cuuint64_t strides[2] = {128, 128 * 513 * 2};
            cuuint32_t box[3] = {64, 8, 4}, es[3] = {1, 1, 1};
            enc(&mp.W[a], CU_TENSOR_MAP_DATA_TYPE_BFLOAT16, 3, (void*)(a ? w_i : w_r), dims, strides, box, es, CU_TENSOR_MAP_INTERLEAVE_NONE, CU_TENSOR_MAP_SWIZZLE_128B,
                CU_TENSOR_MAP_L2_PROMOTION_L2_128B, CU_TENSOR_MAP_FLOAT_OOB_FILL_NONE);
        }
        key[5] = w_r; key[6] = w_i;
        key[0] = x; key[1] = B_re; key[2] = B_im; key[3] = C_re; key[4] = C_im;
    }
    fused_kernel<<<grid, 640, TOT_SMEM, cudaStreamPerThread>>>(mp, x, w_r, w_i, lam_re, lam_im, log_dt, dskip, gate_w, C_re, C_im, B_re, B_im,
        (float*)d_out, grid == NCTA ? NCTA : 0u);
}
```

```cpp
#include <cuda_runtime.h>
#include <cuda_bf16.h>
#include <cuda.h>
#include <stdint.h>

#define ABL 0
#define S_LEN 2048
#define D_DIM 1024
#define P_DIM 1024

namespace ct {
constexpr double PI = 3.14159265358979323846264338327950288;
constexpr double tsin(double x) { double term = x, sum = x; for (int i = 1; i < 12; i++) { term *= -x * x / ((2 * i) * (2 * i + 1)); sum += term; } return sum; }
constexpr double tcos(double x) { double term = 1, sum = 1; for (int i = 1; i < 12; i++) { term *= -x * x / ((2 * i - 1) * (2 * i)); sum += term; } return sum; }
struct CosTab { double v[513]; };
constexpr CosTab make_cos() {
    CosTab t{};
    for (int m = 0; m <= 512; m++) t.v[m] = m == 512 ? 0.0 : (m <= 256 ? tcos(2 * PI * m / 2048.0) : tsin(2 * PI * (512 - m) / 2048.0));
    return t;
}
constexpr CosTab COS = make_cos();
constexpr double cos2048(int m) {
    m &= 2047;
    if (m > 1024) m = 2048 - m;
    if (m > 512) return -COS.v[1024 - m];
    return COS.v[m];
}
constexpr double sin2048(int m) { return cos2048(m - 512); }
constexpr unsigned short bf16bits(double v) {
    if (v == 0.0) return 0;
    unsigned short s = 0;
    if (v < 0) { s = 0x8000; v = -v; }
    int e = 0;
    while (v >= 2.0) { v *= 0.5; e++; }
    while (v < 1.0) { v *= 2.0; e--; }
    double r = v * 128.0;
    int ri = (int)r;
    double fr = r - ri;
    if (fr > 0.5 || (fr == 0.5 && (ri & 1))) ri++;
    if (ri == 256) { ri = 128; e++; }
    return (unsigned short)(s | ((e + 127) << 7) | (ri - 128));
}
constexpr int kmaj(int row, int k, int sbo) { return ((row >> 3) * sbo + (k >> 3) * 128 + (row & 7) * 16 + (k & 7) * 2) >> 1; }
constexpr double rot(int ro, int ri, int a) { return ro == ri ? cos2048(a) : (ro == 0 ? sin2048(a) : -sin2048(a)); }
constexpr int bin(int n) { return (n & 8) | ((n & 3) << 1) | ((n >> 2) & 1); }
constexpr int bout(int n) { return ((n & 2) << 2) | ((n >> 1) & 6) | (n & 1); }
struct Half {
    unsigned short m4[4096];
    unsigned short b16i[1024];
    unsigned short tw[2][128][8];
};
struct Img { unsigned short b16f[1024]; Half h[2]; float cs[16][128][2]; unsigned short m4re[2][4096]; };
constexpr Img make_img() {
    Img t{};
    for (int n = 0; n < 32; n++) for (int k = 0; k < 32; k++) t.b16f[kmaj(n, k, 512)] = bf16bits(rot(((n >> 4) ^ (n >> 3)) & 1, k >> 4, bin(k & 15) * (n & 15) * 128));
    for (int r = 0; r < 16; r++) for (int j = 0; j < 128; j++) { t.cs[r][j][0] = (float)cos2048(16 * j + r); t.cs[r][j][1] = (float)sin2048(16 * j + r); }
    for (int ke = 0; ke < 2; ke++) {
        Half& h = t.h[ke];
        for (int n = 0; n < 32; n++) for (int k = 0; k < 32; k++) h.b16i[kmaj(n, k, 512)] = bf16bits(rot(n >> 4, ((k >> 4) ^ (k >> 3)) & 1, -bout(n & 15) * (k & 15) * 128));
        for (int m = 0; m < 64; m++) for (int k = 0; k < 64; k++) {
            int a = 4 * (m >> 3) + (m & 3), ro = (m >> 2) & 1, kx = 8 * (k >> 4) + (k & 7), ri = (k >> 3) & 1;
            h.m4[kmaj(m, k, 1024)] = bf16bits(rot(ro, ri, -a * (ke + 2 * kx) * 32));
            t.m4re[ke][kmaj(m, k, 1024)] = ro ? 0 : h.m4[kmaj(m, k, 1024)];
        }
        for (int tid = 0; tid < 128; tid++) {
            int kap = ke + 2 * (tid >> 2), q = tid & 3;
            for (int hb = 0; hb < 2; hb++) for (int e = 0; e < 2; e++) {
                int n = 8 * hb + 2 * q + e;
                h.tw[0][tid][4 * hb + e] = bf16bits(cos2048(2 * bin(n) * kap));  h.tw[0][tid][4 * hb + 2 + e] = bf16bits(-sin2048(2 * bin(n) * kap));
                h.tw[1][tid][4 * hb + e] = bf16bits(cos2048(2 * bout(n) * kap)); h.tw[1][tid][4 * hb + 2 + e] = bf16bits(sin2048(2 * bout(n) * kap));
            }
        }
    }
    return t;
}
}
__device__ __align__(128) const ct::Img g_img = ct::make_img();

#define RING 4
#define STGB 32768
#define R0 (4 * 32768)
#define R1 (5 * 32768)
#define R2 (6 * 32768)
#define B16F_OFF (7 * 32768)
#define BAR_OFF (B16F_OFF + 2048)
#define GATE_OFF (BAR_OFF + 256)
#define DSK_OFF (GATE_OFF + 512)
#define TOT_SMEM (DSK_OFF + 256)
#define NCTA 132
#define X2_IMG 36864

__device__ __align__(1024) uint4 g_X1[128 * 2048];
__device__ __align__(1024) uint4 g_X2[128 * X2_IMG / 16];
__device__ __align__(128) float g_gp[256 * 128];
__device__ __align__(1024) uint4 g_h[16 * 32 * 1024];
__device__ __align__(128) unsigned long long g_agg[16 * P_DIM];
__device__ __align__(128) unsigned int g_cnt[8 * 32];
__device__ __align__(1024) __nv_bfloat16 g_Bcopy[2 * P_DIM * D_DIM];
#define g_ticket g_cnt[0]
#define g_cnt1 g_cnt[32]
#define g_cnt2 g_cnt[64]
#define g_cnt3 g_cnt[224]
#define g_cnth(i) g_cnt[96 + 32 * (i)]

#define DBG_END
#define DBG_STAMP(slot)
#define DBG_RAW(slot, v)

__device__ __forceinline__ float bf16r(float v) { return __bfloat162float(__float2bfloat16_rn(v)); }
__device__ __forceinline__ float2 cmul(float2 a, float2 b) { return make_float2(a.x * b.x - a.y * b.y, a.x * b.y + a.y * b.x); }
__device__ __forceinline__ float2 cfma(float2 a, float2 b, float2 c) {
    float re = fmaf(a.x, b.x, c.x); re = fmaf(-a.y, b.y, re);
    float im = fmaf(a.x, b.y, c.y); im = fmaf(a.y, b.x, im);
    return make_float2(re, im);
}
__device__ __forceinline__ uint32_t smem_u32(const void* p) { return (uint32_t)__cvta_generic_to_shared(p); }
__device__ __forceinline__ void bar_sync_n(int id, int n) { asm volatile("bar.sync %0, %1;" :: "r"(id), "r"(n) : "memory"); }
__device__ __forceinline__ void bar_arrive_n(int id, int n) { asm volatile("bar.arrive %0, %1;" :: "r"(id), "r"(n) : "memory"); }
__device__ __forceinline__ uint32_t pack2(float lo, float hi) { uint32_t r; asm("cvt.rn.bf16x2.f32 %0, %1, %2;" : "=r"(r) : "f"(hi), "f"(lo)); return r; }
__device__ __forceinline__ uint64_t mkd(uint32_t b16, uint32_t off, uint32_t lbo, uint32_t sbo, uint32_t swz = 0) {
    uint64_t d;
    asm("mov.b64 %0, {%1, %2};" : "=l"(d) : "r"(b16 + ((off >> 4) + ((lbo >> 4) << 16))), "r"((sbo >> 4) | (swz << 30)));
    return d;
}
__device__ __forceinline__ uint32_t to16(uint32_t saddr) { return 0x40; }
__device__ __forceinline__ void wgmma_fence() { asm volatile("wgmma.fence.sync.aligned;" ::: "memory"); }
__device__ __forceinline__ void wgmma_commit() { asm volatile("wgmma.commit_group.sync.aligned;" ::: "memory"); }
template <int N> __device__ __forceinline__ void wgmma_wait() { asm volatile("wgmma.wait_group.sync.aligned %0;" :: "n"(N) : "memory"); }
__device__ __forceinline__ void fence_async() { asm volatile("fence.proxy.async.shared::cta;" ::: "memory"); }
template <int N> __device__ __forceinline__ void reg_fence(float* d) {
    #pragma unroll
    for (int i = 0; i < N; i++) asm volatile("" : "+f"(d[i]) :: "memory");
}
#define X16(c, d, o) c(d[o]),c(d[o+1]),c(d[o+2]),c(d[o+3]),c(d[o+4]),c(d[o+5]),c(d[o+6]),c(d[o+7]),c(d[o+8]),c(d[o+9]),c(d[o+10]),c(d[o+11]),c(d[o+12]),c(d[o+13]),c(d[o+14]),c(d[o+15])
#define RW(x) "+f"(x)
#define WO(x) "=f"(x)
#define R64(d) X16(RW, d, 0), X16(RW, d, 16), X16(RW, d, 32), X16(RW, d, 48)
#define W64(d) X16(WO, d, 0), X16(WO, d, 16), X16(WO, d, 32), X16(WO, d, 48)
#define R32(d) X16(RW, d, 0), X16(RW, d, 16)
#define W32(d) X16(WO, d, 0), X16(WO, d, 16)
#define R16(d) X16(RW, d, 0)
#define WO16(d) X16(WO, d, 0)
#define L64 "{%0,%1,%2,%3,%4,%5,%6,%7,%8,%9,%10,%11,%12,%13,%14,%15,%16,%17,%18,%19,%20,%21,%22,%23,%24,%25,%26,%27,%28,%29,%30,%31," \
        "%32,%33,%34,%35,%36,%37,%38,%39,%40,%41,%42,%43,%44,%45,%46,%47,%48,%49,%50,%51,%52,%53,%54,%55,%56,%57,%58,%59,%60,%61,%62,%63}"
#define L32 "{%0,%1,%2,%3,%4,%5,%6,%7,%8,%9,%10,%11,%12,%13,%14,%15,%16,%17,%18,%19,%20,%21,%22,%23,%24,%25,%26,%27,%28,%29,%30,%31}"
#define L16 "{%0,%1,%2,%3,%4,%5,%6,%7,%8,%9,%10,%11,%12,%13,%14,%15}"

template <int TA, int TB> __device__ __forceinline__ void ss128(float* d, uint64_t a, uint64_t b) {
    asm volatile("wgmma.mma_async.sync.aligned.m64n128k16.f32.bf16.bf16 " L64 ", %64, %65, 1, 1, 1, %66, %67;\n" : R64(d) : "l"(a), "l"(b), "n"(TA), "n"(TB));
}
template <int TA, int TB> __device__ __forceinline__ void ss128_p(float* d, uint64_t a, uint64_t b, int acc) {
    asm volatile("{\n.reg .pred p;\nsetp.ne.s32 p, %68, 0;\nwgmma.mma_async.sync.aligned.m64n128k16.f32.bf16.bf16 " L64 ", %64, %65, p, 1, 1, %66, %67;\n}\n" : R64(d) : "l"(a), "l"(b), "n"(TA), "n"(TB), "r"(acc));
}
template <int TA, int TB> __device__ __forceinline__ void ss128_z(float* d, uint64_t a, uint64_t b) {
    asm volatile("wgmma.mma_async.sync.aligned.m64n128k16.f32.bf16.bf16 " L64 ", %64, %65, 0, 1, 1, %66, %67;\n" : W64(d) : "l"(a), "l"(b), "n"(TA), "n"(TB));
}
__device__ __forceinline__ void rs64(float* d, uint4 a, uint64_t b) {
    asm volatile("wgmma.mma_async.sync.aligned.m64n64k16.f32.bf16.bf16 " L32 ", {%32,%33,%34,%35}, %36, 1, 1, 1, 0;\n" : R32(d) : "r"(a.x), "r"(a.y), "r"(a.z), "r"(a.w), "l"(b));
}
__device__ __forceinline__ void rs64_z(float* d, uint4 a, uint64_t b) {
    asm volatile("wgmma.mma_async.sync.aligned.m64n64k16.f32.bf16.bf16 " L32 ", {%32,%33,%34,%35}, %36, 0, 1, 1, 0;\n" : W32(d) : "r"(a.x), "r"(a.y), "r"(a.z), "r"(a.w), "l"(b));
}
__device__ __forceinline__ void rs32(float* d, uint32_t a0, uint32_t a1, uint32_t a2, uint32_t a3, uint64_t b) {
    asm volatile("wgmma.mma_async.sync.aligned.m64n32k16.f32.bf16.bf16 " L16 ", {%16,%17,%18,%19}, %20, 1, 1, 1, 0;\n"
        : R16(d) : "r"(a0), "r"(a1), "r"(a2), "r"(a3), "l"(b));
}
__device__ __forceinline__ void rs32_z(float* d, uint32_t a0, uint32_t a1, uint32_t a2, uint32_t a3, uint64_t b) {
    asm volatile("wgmma.mma_async.sync.aligned.m64n32k16.f32.bf16.bf16 " L16 ", {%16,%17,%18,%19}, %20, 0, 1, 1, 0;\n"
        : WO16(d) : "r"(a0), "r"(a1), "r"(a2), "r"(a3), "l"(b));
}
__device__ __forceinline__ void stsm_x4(uint32_t addr, uint32_t r0, uint32_t r1, uint32_t r2, uint32_t r3) {
    asm volatile("stmatrix.sync.aligned.m8n8.x4.shared.b16 [%0], {%1, %2, %3, %4};" :: "r"(addr), "r"(r0), "r"(r1), "r"(r2), "r"(r3) : "memory");
}
__device__ __forceinline__ uint32_t lds32(uint32_t a) { uint32_t v; asm volatile("ld.shared.u32 %0, [%1];" : "=r"(v) : "r"(a) : "memory"); return v; }
__device__ __forceinline__ uint2 lds64(uint32_t a) { uint2 v; asm volatile("ld.shared.v2.u32 {%0, %1}, [%2];" : "=r"(v.x), "=r"(v.y) : "r"(a) : "memory"); return v; }
__device__ __forceinline__ uint4 lds128(uint32_t a) { uint4 v; asm volatile("ld.shared.v4.u32 {%0, %1, %2, %3}, [%4];" : "=r"(v.x), "=r"(v.y), "=r"(v.z), "=r"(v.w) : "r"(a) : "memory"); return v; }
__device__ __forceinline__ void sts32(uint32_t a, uint32_t x) { asm volatile("st.shared.u32 [%0], %1;" :: "r"(a), "r"(x) : "memory"); }
__device__ __forceinline__ void sts128(uint32_t a, uint32_t x, uint32_t y, uint32_t z, uint32_t w) {
    asm volatile("st.shared.v4.u32 [%0], {%1, %2, %3, %4};" :: "r"(a), "r"(x), "r"(y), "r"(z), "r"(w) : "memory");
}
__device__ __forceinline__ float bflo(uint32_t v) { return __uint_as_float(v << 16); }
__device__ __forceinline__ float bfhi(uint32_t v) { return __uint_as_float(v & 0xffff0000u); }
__device__ __forceinline__ uint32_t hmul2bf(uint32_t a, uint32_t b) { uint32_t r; asm("mul.rn.bf16x2 %0, %1, %2;" : "=r"(r) : "r"(a), "r"(b)); return r; }
__device__ __forceinline__ uint32_t hadd2bf(uint32_t a, uint32_t b) { uint32_t r; asm("add.rn.bf16x2 %0, %1, %2;" : "=r"(r) : "r"(a), "r"(b)); return r; }
__device__ __forceinline__ uint32_t hsub2bf(uint32_t a, uint32_t b) { uint32_t r; asm("sub.rn.bf16x2 %0, %1, %2;" : "=r"(r) : "r"(a), "r"(b)); return r; }
__device__ __forceinline__ void mbar_init(uint32_t a, uint32_t c) { asm volatile("mbarrier.init.shared.b64 [%0], %1;" :: "r"(a), "r"(c)); }
__device__ __forceinline__ void mbar_wait(uint32_t a, uint32_t ph) {
    asm volatile("{\n.reg .pred p;\n.reg .u32 n;\nmov.u32 n, 0;\nWAIT_LOOP:\nmbarrier.try_wait.parity.shared.b64 p, [%0], %1;\n@p bra DONE;\nadd.u32 n, n, 1;\nsetp.lt.u32 p, n, 4000000;\n@p bra WAIT_LOOP;\nDONE:\n}" :: "r"(a), "r"(ph) : "memory");
}
__device__ __forceinline__ void mbar_wait_n(uint32_t a, uint32_t ph, uint32_t& n) {
    asm volatile("{\n.reg .pred p;\nWAIT_LOOP:\nmbarrier.try_wait.parity.shared.b64 p, [%1], %2;\n@p bra DONE;\nadd.u32 %0, %0, 1;\nsetp.lt.u32 p, %0, 4000000;\n@p bra WAIT_LOOP;\nDONE:\n}" : "+r"(n) : "r"(a), "r"(ph) : "memory");
}
__device__ __forceinline__ bool mbar_test(uint32_t a, uint32_t ph) {
    uint32_t r;
    asm volatile("{\n.reg .pred p;\nmbarrier.test_wait.parity.shared.b64 p, [%1], %2;\nselp.u32 %0, 1, 0, p;\n}" : "=r"(r) : "r"(a), "r"(ph) : "memory");
    return __all_sync(0xffffffffu, r != 0);
}
__device__ __forceinline__ void mbar_expect_tx(uint32_t a, uint32_t bytes) { asm volatile("mbarrier.arrive.expect_tx.shared.b64 _, [%0], %1;" :: "r"(a), "r"(bytes) : "memory"); }
__device__ __forceinline__ void mbar_arrive(uint32_t a) { asm volatile("mbarrier.arrive.shared.b64 _, [%0];" :: "r"(a) : "memory"); }
__device__ __forceinline__ void mbar_arrive8(uint32_t a) { asm volatile("mbarrier.arrive.shared.b64 _, [%0], 8;" :: "r"(a) : "memory"); }
__device__ __forceinline__ void mbar_arrive2(uint32_t a) { asm volatile("mbarrier.arrive.shared.b64 _, [%0], 2;" :: "r"(a) : "memory"); }
__device__ __forceinline__ void tma_load_2d(uint32_t dst, const CUtensorMap* map, int c0, int c1, uint32_t bar) {
    asm volatile("cp.async.bulk.tensor.2d.shared::cluster.global.mbarrier::complete_tx::bytes [%0], [%1, {%3, %4}], [%2];"
        :: "r"(dst), "l"(map), "r"(bar), "r"(c0), "r"(c1) : "memory");
}
__device__ __forceinline__ void tma_load_3d(uint32_t dst, const CUtensorMap* map, int c0, int c1, int c2, uint32_t bar) {
    asm volatile("cp.async.bulk.tensor.3d.shared::cluster.global.mbarrier::complete_tx::bytes [%0], [%1, {%3, %4, %5}], [%2];"
        :: "r"(dst), "l"(map), "r"(bar), "r"(c0), "r"(c1), "r"(c2) : "memory");
}
__device__ __forceinline__ void tma_load_4d(uint32_t dst, const CUtensorMap* map, int c0, int c3, uint32_t bar) {
    asm volatile("cp.async.bulk.tensor.4d.shared::cluster.global.mbarrier::complete_tx::bytes [%0], [%1, {%3, %5, %5, %4}], [%2];"
        :: "r"(dst), "l"(map), "r"(bar), "r"(c0), "r"(c3), "r"(0) : "memory");
}
__device__ __forceinline__ void tma_load_5d(uint32_t dst, const CUtensorMap* map, int c0, int c4, uint32_t bar) {
    asm volatile("cp.async.bulk.tensor.5d.shared::cluster.global.mbarrier::complete_tx::bytes [%0], [%1, {%3, %5, %5, %5, %4}], [%2];"
        :: "r"(dst), "l"(map), "r"(bar), "r"(c0), "r"(c4), "r"(0) : "memory");
}
__device__ __forceinline__ void bulk_load(uint32_t dst, const void* src, uint32_t bytes, uint32_t bar) {
    asm volatile("cp.async.bulk.shared::cluster.global.mbarrier::complete_tx::bytes [%0], [%1], %2, [%3];" :: "r"(dst), "l"(src), "r"(bytes), "r"(bar) : "memory");
}
__device__ __forceinline__ void l2_prefetch(const void* p, uint32_t bytes) {
    asm volatile("cp.async.bulk.prefetch.L2.global [%0], %1;" :: "l"(p), "r"(bytes) : "memory");
}
__device__ __forceinline__ void wait_counter(const unsigned int* p, unsigned int target) {
    unsigned int cur; int spins = 0;
    #pragma unroll 1
    do {
        asm volatile("ld.relaxed.gpu.global.u32 %0, [%1];" : "=r"(cur) : "l"(p) : "memory");
        if ((int)(cur - target) >= 0) break;
        __nanosleep(20);
    } while (++spins < (1 << 22));
}
__device__ __forceinline__ void red_release(unsigned int* p) { asm volatile("red.release.gpu.global.add.u32 [%0], 1;" :: "l"(p) : "memory"); }
__device__ __forceinline__ uint32_t clk32() { uint32_t c; asm volatile("mov.u32 %0, %%clock;" : "=r"(c)); return c; }
__device__ __forceinline__ bool elect_one() {
    uint32_t r;
    asm volatile("{\n.reg .pred p;\nelect.sync _|p, 0xffffffff;\nselp.u32 %0, 1, 0, p;\n}" : "=r"(r));
    return r != 0;
}
#define PAUSE_NS 0
__device__ __forceinline__ void pause() { __nanosleep(PAUSE_NS); }
__device__ __forceinline__ int tid128() { int t; asm volatile("mov.u32 %0, %%tid.x;" : "=r"(t)); return t & 127; }
#define CTW(yr, yi, qx, qy) do { const float _r = (yr), _i = (yi); yr = _r * (qx) - _i * (qy); yi = _r * (qy) + _i * (qx); } while (0)
typedef __nv_bfloat162 bf2;
__device__ __forceinline__ bf2 asbf2(uint32_t v) { return *reinterpret_cast<bf2*>(&v); }
__device__ __forceinline__ uint32_t asu32(bf2 v) { return *reinterpret_cast<uint32_t*>(&v); }
template <int M> struct W16 { static constexpr uint32_t c = ct::bf16bits(ct::cos2048(128 * M)) * 0x10001u, s = ct::bf16bits(-ct::sin2048(128 * M)) * 0x10001u; };
__device__ __forceinline__ void pin(bf2& v) { uint32_t u = asu32(v); asm volatile("" : "+r"(u) :: "memory"); v = asbf2(u); }
__device__ __forceinline__ bf2 neg2(bf2 v) { return asbf2(asu32(v) ^ 0x80008000u); }
__device__ __forceinline__ void cmul2(bf2& r, bf2& i, bf2 wr, bf2 wi) {
    const bf2 a = r, b = i;
    r = __hfma2(a, wr, __hmul2(b, neg2(wi))); i = __hfma2(b, wr, __hmul2(a, wi));
}
__device__ __forceinline__ void bfly4(bf2* r, bf2* i, int o, int s) {
    const bf2 ar = __hadd2(r[o], r[o + 2 * s]), ai = __hadd2(i[o], i[o + 2 * s]), br = __hsub2(r[o], r[o + 2 * s]), bi = __hsub2(i[o], i[o + 2 * s]);
    const bf2 cr = __hadd2(r[o + s], r[o + 3 * s]), ci = __hadd2(i[o + s], i[o + 3 * s]), dr = __hsub2(r[o + s], r[o + 3 * s]), di = __hsub2(i[o + s], i[o + 3 * s]);
    r[o] = __hadd2(ar, cr); i[o] = __hadd2(ai, ci); r[o + 2 * s] = __hsub2(ar, cr); i[o + 2 * s] = __hsub2(ai, ci);
    r[o + s] = __hadd2(br, di); i[o + s] = __hsub2(bi, dr); r[o + 3 * s] = __hsub2(br, di); i[o + 3 * s] = __hadd2(bi, dr);
}
template <int M> __device__ __forceinline__ void tw16(bf2& r, bf2& i) {
    if (M == 4) { const bf2 a = r; r = i; i = neg2(a); }
    else cmul2(r, i, asbf2(W16<M>::c), asbf2(W16<M>::s));
}
__device__ __forceinline__ void tw16_all(bf2* r, bf2* i) {
    tw16<1>(r[5], i[5]); tw16<2>(r[6], i[6]); tw16<3>(r[7], i[7]); tw16<2>(r[9], i[9]); tw16<4>(r[10], i[10]); tw16<6>(r[11], i[11]);
    tw16<3>(r[13], i[13]); tw16<6>(r[14], i[14]); tw16<9>(r[15], i[15]);
}

__device__ __forceinline__ void dft16(bf2* r, bf2* i) {
    #pragma unroll
    for (int r0 = 0; r0 < 4; r0++) bfly4(r, i, r0, 4);
    tw16_all(r, i);
    #pragma unroll
    for (int k1 = 0; k1 < 4; k1++) bfly4(r, i, 4 * k1, 1);
}
__device__ __forceinline__ void idft16(bf2* r, bf2* i) {
    #pragma unroll
    for (int k1 = 0; k1 < 4; k1++) bfly4(i, r, 4 * k1, 1);
    tw16_all(i, r);
    #pragma unroll
    for (int r0 = 0; r0 < 4; r0++) bfly4(i, r, r0, 4);
}

#define DBAR 1
#define FBAR 2
#define SBAR 3
#define HBAR 6
#define WBAR 4
#define ZBAR 5
#define FULL(s) (bars + 8 * (s))
#define EMPTY(s) (bars + 8 * (RING + (s)))
#define XB (bars + 64)
#define X1B (bars + 72)
#define WQ(i) (bars + 144 + 8 * ((i) & 1))
#define ZB (bars + 88)
#define EPB (bars + 96)
#define R0F (bars + 104)
#define HOK(i) (bars + 112 + 8 * (i))
#define EPO_OFF (BAR_OFF + 160)
#define ROLE_OFF (BAR_OFF + 164)
#define SACT_OFF (BAR_OFF + 176)
#define LBAR 12
#define PSZ 8192
#define BND 2
#define PHOLD 0
#define PBAR 0
#define X1C (bars + 168)
#define PC1M 256
#define P1END 8500
#define LAM_OFF (R2 + 27648)
#define PCW3 200
#define PCW 200
#define PT_OFF (R2 + 26624)
#define WBUF(i) ((i) == 1 ? R1 : ((i) == 2 ? R1 + 16384 : R2 + 10240))
#define PC1 448
#define PC2 88
#define PCH 96
#define PCL 100
__device__ __forceinline__ void delay(int cycles) { if (cycles > 0) { const uint32_t c = clk32(); while ((int)(clk32() - c) < cycles) { } } }
__device__ __forceinline__ void pace(uint32_t& t, int cycles) { if (cycles == 0) return; while ((int)(clk32() - t) < 0) { } t += cycles; }
__device__ __forceinline__ void pf_line(const void* p) { asm volatile("prefetch.global.L2 [%0];" :: "l"(p)); }

__device__ __forceinline__ float2 cis(int m) { return __ldg(reinterpret_cast<const float2*>(g_img.cs[m & 15][(m >> 4) & 127])); }
__device__ __forceinline__ void gen_dft(uint32_t dst, int j, float2 w, float2 b, int b0, int b1, float c0) {
    const float c2 = 2.f * w.x;
    float2 a = cmul(b, w);
    float2 z0 = b0 ? b : make_float2(c0, (j & 1) ? -c0 : c0);
    dst += j * 128;
    #pragma unroll 1
    for (int blk = b0; blk < b1; blk++) {
        float2 v[9];
        v[0] = b;
        v[1] = make_float2(fmaf(c2, b.x, -a.x), fmaf(c2, b.y, -a.y));
        #pragma unroll
        for (int k = 2; k < 9; k++) v[k] = make_float2(fmaf(c2, v[k - 1].x, -v[k - 2].x), fmaf(c2, v[k - 1].y, -v[k - 2].y));
        const uint32_t p = dst + (blk >> 2) * 16384, c = (2 * (blk & 3)) ^ (j & 7);
        sts128(p + c * 16, pack2(z0.x, v[1].x), pack2(v[2].x, v[3].x), pack2(v[4].x, v[5].x), pack2(v[6].x, v[7].x));
        sts128(p + (c ^ 1) * 16, pack2(z0.y, v[1].y), pack2(v[2].y, v[3].y), pack2(v[4].y, v[5].y), pack2(v[6].y, v[7].y));
        a = v[7]; b = v[8]; z0 = b;
    }
}

__device__ __forceinline__ void fft_p1(uint32_t sbase, int tile, int r, int db, uint32_t t_end) {
    const uint32_t s16 = to16(sbase);
    float acc[64];
    wgmma_fence();
    ss128_z<1, 1>(acc, mkd(s16 + tile * 1024, R1, 16384, 1024, 1), mkd(s16, R0, 16384, 1024, 1));
    #pragma unroll
    for (int ks = 1; ks < 8; ks++) ss128<1, 1>(acc, mkd(s16 + tile * 1024, R1 + ks * 2048, 16384, 1024, 1), mkd(s16, R0 + ks * 2048, 16384, 1024, 1));
    wgmma_commit();
    const int tid = tid128();
    float g0 = 0.f;
    uint4* dst = g_X1 + (64 * tile + 2 * (tid >> 2)) * 2048 + (r >> 3) * 1024 + db * 128 + (r & 7) * 16 + (tid & 3);
    wgmma_wait<0>();
    reg_fence<64>(acc);
    if (tid == 0) DBG_STAMP(116 + tile);
    if (PHOLD) bar_arrive_n(PBAR, 512);
    uint32_t tp = clk32();
    const int dt = min(max((int)(t_end - tp) >> 3, PC1M), PC1);
    tp += (threadIdx.x >> 5 & 7) * (dt >> 3);
    #pragma unroll
    for (int c = 0; c < 4; c++) {
        const float* u = acc + 4 * (c >> 1) + (c & 1);
        #pragma unroll
        for (int ke = 0; ke < 2; ke++) {
            float v[8];
            #pragma unroll
            for (int z = 0; z < 8; z++) { const int ix = 8 * (z & 3) + 2 * (z >> 2); v[z] = ke ? u[ix] - u[ix + 32] : u[ix] + u[ix + 32]; }
            uint4 o = make_uint4(pack2(v[0], v[1]), pack2(v[2], v[3]), pack2(v[4], v[5]), pack2(v[6], v[7]));
            asm volatile("" : "+r"(o.x), "+r"(o.y), "+r"(o.z), "+r"(o.w) :: "memory");
            pace(tp, dt);
            __stcg(dst + ke * 2048 + 4 * c, o);
            if (c < 2) {
                #pragma unroll
                for (int k = 4 * c + 2 * ke; k < 4 * c + 2 * ke + 2; k++) {
                    const uint4 x = lds128(sbase + R0 + tile * 16384 + tid * 128 + ((k ^ (tid & 7)) << 4)), gv = lds128(sbase + GATE_OFF + tile * 128 + k * 16);
                    const uint32_t p0 = hmul2bf(x.x, gv.x), p1 = hmul2bf(x.y, gv.y), p2 = hmul2bf(x.z, gv.z), p3 = hmul2bf(x.w, gv.w);
                    g0 += ((bflo(p0) + bfhi(p0)) + (bflo(p1) + bfhi(p1))) + ((bflo(p2) + bfhi(p2)) + (bflo(p3) + bfhi(p3)));
                }
            }
            if (c == 1 && ke == 1) {
                __stcg(&g_gp[(16 * r + 2 * db + tile) * 128 + tid], g0);
                __syncwarp();
                if ((tid & 31) == 0) mbar_arrive(sbase + BAR_OFF + 104);
            }
        }
    }
}

__device__ __forceinline__ int w_first(int unit, int hb) { const int ka = unit >> 1, ke = unit & 1; return hb ? ((128 - ka) & 127) * 513 + 2 - ke : ka * 513 + ke; }
__device__ __forceinline__ void load_w(const CUtensorMap* wm, uint32_t sbase, int unit, int i) {
    const uint32_t bars = sbase + BAR_OFF;
    mbar_expect_tx(WQ(i), 16384);
    #pragma unroll 1
    for (int a = 0; a < 4; a++) {
        asm volatile("cp.async.bulk.tensor.3d.shared::cluster.global.mbarrier::complete_tx::bytes [%0], [%1, {%3, %4, %5}], [%2];"
            :: "r"(sbase + WBUF(i) + a * 4096), "l"(wm + (i & 1)), "r"(WQ(i)), "r"(w_first(unit, i >> 1) & ~15), "r"(0), "r"(4 * a) : "memory");
        delay(i == 3 ? PCW3 : PCW);
    }
}
__device__ __forceinline__ uint32_t w_off(int e) { e &= 511; return (e >> 6) * 128 + ((((e >> 3) ^ (e >> 6)) & 7) << 4) + (e & 7) * 2; }
__device__ __forceinline__ void sts16(uint32_t a, uint32_t v) { asm volatile("st.shared.u16 [%0], %1;" :: "r"(a), "h"((unsigned short)v) : "memory"); }
__device__ __forceinline__ void load_paced(uint32_t dst, const uint8_t* src, int n, uint32_t bar) {
    #pragma unroll 1
    for (int i = 0; i < n; i++) { bulk_load(dst + i * PSZ, src + i * PSZ, PSZ, bar); delay(PCL); }
}
__device__ __forceinline__ void boundary() { while (clk32() == 0) { } asm volatile("" ::: "memory"); }
__device__ __forceinline__ void yield_to_scan(uint32_t sbase) {
    #pragma unroll 1
    for (int n = 0; n < 100000 && lds32(sbase + SACT_OFF); n++) __nanosleep(50);
}
template <int OFF> __device__ __forceinline__ uint32_t lds_w(uint32_t a, uint32_t b) {
    uint32_t l, h;
    asm volatile("ld.shared.u16 %0, [%2 + %4];\nld.shared.u16 %1, [%3 + %4];" : "=r"(l), "=r"(h) : "r"(a), "r"(b), "n"(OFF) : "memory");
    return __byte_perm(l, h, 0x5410);
}
template <int S> __device__ __forceinline__ void load_ws(uint32_t* w, uint32_t a, uint32_t b) {
    if constexpr (S < 16) { w[S] = lds_w<((S >> 2) + 4 * (S & 3)) * 1024>(a, b); load_ws<S + 1>(w, a, b); }
}
template <int TB> __device__ __forceinline__ void ss64(float* d, uint64_t a, uint64_t b) {
    asm volatile("wgmma.mma_async.sync.aligned.m64n64k16.f32.bf16.bf16 " L32 ", %32, %33, 1, 1, 1, 0, %34;\n" : R32(d) : "l"(a), "l"(b), "n"(TB));
}
template <int TB> __device__ __forceinline__ void ss64_z(float* d, uint64_t a, uint64_t b) {
    asm volatile("wgmma.mma_async.sync.aligned.m64n64k16.f32.bf16.bf16 " L32 ", %32, %33, 0, 1, 1, 0, %34;\n" : W32(d) : "l"(a), "l"(b), "n"(TB));
}

template <int I> __device__ __forceinline__ void fetch_w(uint32_t* w, uint32_t sbase, int unit) {
    constexpr int hb = I >> 1;
    const uint32_t bars = sbase + BAR_OFF, buf = sbase + WBUF(I);
    const int tid = tid128(), sh = w_first(unit, hb) & 15;
    const uint32_t pt = lds32(sbase + PT_OFF + 512 * hb + 4 * tid) >> (16 * (I & 1)), sp = lds32(sbase + DSK_OFF + 4 * (tid & 31)) >> (16 * (I & 1));
    mbar_wait(WQ(I), hb);
    if ((sh & 1) + 2 * (tid & 7) + 2 <= sh) sts16(buf + (tid >> 3) * 1024 + ((sh & 1) + 2 * (tid & 7)) * 2, pt);
    bar_sync_n(FBAR, 128);
    if (!(unit & 1) && (tid >> 4) == hb) sts16(buf + w_off(sh + 510 * hb) + (tid & 15) * 1024, sp);
    __syncwarp();
    boundary();
    const int pos = 128 * (tid & 3) + 2 * (tid >> 2);
    const bool rot = hb && unit >= 2;
    const uint32_t o0 = buf + w_off(sh + (hb ? 510 - pos : pos)) - (rot ? 1024 : 0), o1 = buf + w_off(sh + (hb ? 446 - pos : pos + 64)) - (rot ? 1024 : 0), oz = rot ? 16384 : 0;
    w[0] = lds_w<0>(o0 + oz, o1 + oz);
    load_ws<1>(w, o0, o1);
}
__device__ __forceinline__ void pin16(bf2* r, bf2* i) {
    #pragma unroll
    for (int k = 0; k < 16; k++) { pin(r[k]); pin(i[k]); }
}

__device__ __forceinline__ void fft_p2(uint32_t sbase, uint32_t bars, int unit, const __nv_bfloat16* w_r, const __nv_bfloat16* w_i) {
    const uint32_t s16 = to16(sbase);
    const ct::Half* tb = &g_img.h[unit & 1];
    uint32_t P[16][4];
    uint32_t wr[16], wi[16];
    {
        const int tid = tid128();
        uint32_t sp = 0, pt[2] = {0, 0};
        const uint4 t = __ldg(reinterpret_cast<const uint4*>(tb->tw[0][tid]));
        if (tid < 32 && !(unit & 1)) {
            const int k1 = ((tid & 16) ? (128 - (unit >> 1)) & 127 : unit >> 1) + 128 * (tid & 15), o1 = k1 * 513 + 32 * (tid & 16), o2 = ((2048 - k1) & 2047) * 513 + 32 * (tid & 16);
            sp = pack2(0.5f * (__bfloat162float(w_r[o1]) + __bfloat162float(w_r[o2])), 0.5f * (__bfloat162float(w_i[o1]) - __bfloat162float(w_i[o2])));
        }
        #pragma unroll
        for (int hb = 0; hb < 2; hb++) {
            const int e0 = w_first(unit, hb), z = (e0 & 1) + 2 * (tid & 7), o = (tid >> 3) * 65664 + (e0 & ~15) + 512 + z;
            if (z + 2 <= (e0 & 15)) pt[hb] = reinterpret_cast<const unsigned short*>(w_r)[o] | ((uint32_t)reinterpret_cast<const unsigned short*>(w_i)[o] << 16);
        }
        sts32(sbase + PT_OFF + 4 * tid, pt[0]); sts32(sbase + PT_OFF + 512 + 4 * tid, pt[1]);
        mbar_wait(X1B, 0);
        if (tid < 32) sts32(sbase + DSK_OFF + 4 * tid, sp);
        if (unit >= 128) {
            mbar_wait(X1C, 0);
            #pragma unroll 1
            for (int i = 0; i < 16; i++) {
                const float2 w = cis(-64 * ((i & 8) + (tid >> 4)));
                const uint32_t a = sbase + R1 + (i * 128 + tid) * 16;
                const uint2 v = lds64(a + 8);
                sts128(a, pack2(bflo(v.x) * w.x, bfhi(v.x) * w.x), pack2(bflo(v.y) * w.x, bfhi(v.y) * w.x), pack2(bflo(v.x) * w.y, bfhi(v.x) * w.y), pack2(bflo(v.y) * w.y, bfhi(v.y) * w.y));
            }
            fence_async();
            bar_sync_n(FBAR, 128);
        }
        if (tid == 0) DBG_STAMP(17);
        #pragma unroll
        for (int h = 0; h < 2; h++) {
            float acc[64];
            if (h) mbar_wait(X1C, 0);
            wgmma_fence();
            ss128_z<1, 0>(acc, mkd(s16, R2, 1024, 128), mkd(s16, R1 + h * 16384, 2048, 128));
            #pragma unroll
            for (int s = 1; s < 4; s++) ss128<1, 0>(acc, mkd(s16, R2 + s * 2048, 1024, 128), mkd(s16, R1 + h * 16384 + s * 4096, 2048, 128));
            wgmma_commit();
            if (h == 1) {
                fetch_w<0>(wr, sbase, unit);
                #pragma unroll
                for (int s = 0; s < 16; s++) asm volatile("" : "+r"(wr[s]) :: "memory");
                if (unit > 999) sts32(sbase + SACT_OFF + 4, wr[15]);
            }
            wgmma_wait<0>();
            reg_fence<64>(acc);
            bar_arrive_n(LBAR + h, 160);
            bf2 f[32];
            #pragma unroll
            for (int z = 0; z < 32; z++) { uint32_t u = pack2(acc[2 * z], acc[2 * z + 1]); asm volatile("" : "+r"(u) :: "memory"); f[z] = asbf2(u); }
            boundary();
            float d[2][16];
            #pragma unroll
            for (int pr = 0; pr < 5; pr++) {
                if (pr == 2) boundary();
                if (pr < 4) {
                    bf2* a = f + 8 * pr;
                    #pragma unroll
                    for (int z = 0; z < 8; z++) pin(a[z]);
                    #pragma unroll
                    for (int z = 0; z < 4; z++) cmul2(a[2 * z], a[2 * z + 1], asbf2((z & 1) ? t.z : t.x), asbf2((z & 1) ? t.w : t.y));
                    wgmma_fence();
                    rs32_z(d[pr & 1], asu32(a[0]), asu32(a[4]), asu32(a[2]), asu32(a[6]), mkd(s16, B16F_OFF, 128, 512));
                    rs32(d[pr & 1], asu32(a[1]), asu32(a[5]), asu32(a[3]), asu32(a[7]), mkd(s16, B16F_OFF + 256, 128, 512));
                    wgmma_commit();
                }
                if (pr > 0) {
                    if (pr < 4) wgmma_wait<1>(); else wgmma_wait<0>();
                    reg_fence<16>(d[(pr - 1) & 1]);
                    #pragma unroll
                    for (int z = 0; z < 8; z++) {
                        uint32_t& p = P[8 * h + 2 * pr - 2 + (z & 1)][z >> 1];
                        p = pack2(d[(pr - 1) & 1][2 * z], d[(pr - 1) & 1][2 * z + 1]);
                        asm volatile("" : "+r"(p) :: "memory");
                    }
                }
            }
        }
    }
    if (tid128() == 0) DBG_STAMP(18);
    {
        bf2 vr[2][16], vi[2][16];
        #pragma unroll
        for (int r = 0; r < 16; r++) { vr[0][r] = asbf2(P[r][0]); vr[1][r] = asbf2(P[r][1]); vi[0][r] = asbf2(P[r][2]); vi[1][r] = asbf2(P[r][3]); }
        fetch_w<1>(wi, sbase, unit);
        pin16(vr[0], vi[0]);
        dft16(vr[0], vi[0]);
        #pragma unroll
        for (int s = 0; s < 16; s++) cmul2(vr[0][s], vi[0][s], asbf2(wr[s]), asbf2(wi[s]));
        fetch_w<2>(wr, sbase, unit);
        pin16(vr[1], vi[1]);
        dft16(vr[1], vi[1]);
        fetch_w<3>(wi, sbase, unit);
        pin16(vr[0], vi[0]);
        idft16(vr[0], vi[0]);
        #pragma unroll
        for (int s = 0; s < 16; s++) cmul2(vr[1][s], vi[1][s], asbf2(wr[s]), asbf2(wi[s]));
        bar_sync_n(FBAR, 128);
        idft16(vr[1], vi[1]);
        #pragma unroll
        for (int r = 0; r < 16; r++) { P[r][0] = asu32(vr[0][r]); P[r][1] = asu32(vr[1][r]); P[r][2] = asu32(vi[0][r]); P[r][3] = asu32(vi[1][r]); }
    }
    if (tid128() == 0) DBG_STAMP(19);
    {
        const int tid = tid128();
        const uint4 t = __ldg(reinterpret_cast<const uint4*>(tb->tw[1][tid]));
        const uint32_t zero = unit >> 8;
        const uint32_t sa = sbase + R1 + ((tid >> 3) & 1) * 1024 + (2 * (tid >> 5) + ((tid >> 4) & 1)) * 128 + (tid & 7) * 16;
        float acc[2][16];
        #pragma unroll
        for (int pr = 0; pr < 9; pr++) {
            if (BND && (pr % BND) == 0) boundary();
            if (pr < 8) {
                uint32_t a[8];
                #pragma unroll
                for (int z = 0; z < 8; z++) asm volatile("xor.b32 %0, %1, %2;" : "=r"(a[z]) : "r"(P[2 * pr + (z >> 2)][z & 3]), "r"(zero) : "memory");
                wgmma_fence();
                rs32_z(acc[pr & 1], a[0], a[4], a[1], a[5], mkd(s16, R2 + 8192, 128, 512));
                rs32(acc[pr & 1], a[2], a[6], a[3], a[7], mkd(s16, R2 + 8192 + 256, 128, 512));
                wgmma_commit();
            }
            if (pr > 0) {
                if (pr < 8) wgmma_wait<1>(); else wgmma_wait<0>();
                reg_fence<16>(acc[(pr - 1) & 1]);
                #pragma unroll
                for (int rl = 0; rl < 2; rl++) {
                    const float* a = acc[(pr - 1) & 1] + 2 * rl;
                    bf2 r0 = asbf2(pack2(a[0], a[1])), r1 = asbf2(pack2(a[4], a[5])), i0 = asbf2(pack2(a[8], a[9])), i1 = asbf2(pack2(a[12], a[13]));
                    cmul2(r0, i0, asbf2(t.x), asbf2(t.y)); cmul2(r1, i1, asbf2(t.z), asbf2(t.w));
                    stsm_x4(sa + (2 * pr - 2 + rl) * 2048, asu32(r0), asu32(r1), asu32(i0), asu32(i1));
                }
            }
        }
    }
    fence_async();
    bar_sync_n(FBAR, 128);
    if (tid128() == 0) DBG_STAMP(20);
    {
        const int tid = tid128(), ka = unit >> 1;
        uint8_t* dst = reinterpret_cast<uint8_t*>(g_X2) + (2 * (tid >> 5)) * X2_IMG + (unit & 1) * (X2_IMG / 2)
                     + (16 * (ka >> 3) + 8 * ((tid >> 4) & 1) + (ka & 7)) * 128 + ((((tid >> 1) & 7) ^ (ka & 7)) << 4) + (tid & 1) * 8;
        float acc[64];
        uint32_t o[32], tp = 0;
        #pragma unroll
        for (int h = 0; h < 3; h++) {
            if (h < 2) {
                wgmma_fence();
                ss128_z<0, 1>(acc, mkd(s16, R2, 128, 1024), mkd(s16, R1 + h * 16384, 128, 1024));
                #pragma unroll
                for (int s = 1; s < 4; s++) ss128<0, 1>(acc, mkd(s16, R2 + s * 256, 128, 1024), mkd(s16, R1 + h * 16384 + s * 256, 128, 1024));
                wgmma_commit();
            }
            if (h > 0) {
                yield_to_scan(sbase);
                if (h == 1 || (int)(clk32() - tp) > PC2) tp = clk32() + (tid >> 5) * (PC2 / 2);
                #pragma unroll
                for (int z = 0; z < 16; z++) { if (!(z & 1)) pace(tp, 2 * PC2); __stcg(reinterpret_cast<uint2*>(dst + (64 * h - 64 + 8 * (z >> 1) + (z & 1)) * X2_IMG), make_uint2(o[2 * z], o[2 * z + 1])); }
            }
            if (h < 2) {
                wgmma_wait<0>();
                reg_fence<64>(acc);
                #pragma unroll
                for (int z = 0; z < 16; z++) { const float* a = acc + 8 * (z >> 1) + 2 * (z & 1); o[2 * z] = pack2(a[0], a[1]); o[2 * z + 1] = pack2(a[4], a[5]); asm volatile("" : "+r"(o[2 * z]), "+r"(o[2 * z + 1]) :: "memory"); }
                boundary();
            }
        }
    }
}

struct Maps { CUtensorMap BB, X, Xr, Cre, Cim, W[2]; };
#define PSL 100
#define MAPV 0
#define SP1 0
#define SP2 2
#define GBAR 10
#define KBAR 11
#define HOLD -1
#define EAGG 8
#define YP1 1
#define PCR 96
#define PCG 0
#define YIELD 1u
#define ZOK (bars + 80)
#define TBAR 4
#define STAG 2
#define TTAB 8500
#define W0E 0
#define DBGS 3
#define SHP 1
#define REL2 1
#define SBV 1
#define TST 0
#define EPF 1
#define PF2 0
#define TXT 0
#define PF3 800
#define NPF 3
#define XRS 150
#define STG1 0
#define PD0 20
#define PFC 12000
#define PFCS 2000
#define PFX 6
#define PFW 5000
#define PFB 9000

#define SBASE 0x400u
template <int S> __device__ __forceinline__ void release(uint32_t rel, uint32_t bars) {
    if (REL2) mbar_arrive(EMPTY(S));
    asm volatile("mbarrier.arrive.shared::cluster.b64 _, [%0 + %1];" :: "r"(rel), "n"(8 * (RING + S)) : "memory");
}
__device__ __forceinline__ int peer_role(uint32_t a) { int v; asm volatile("ld.shared::cluster.u32 %0, [%1];" : "=r"(v) : "r"(a ^ (1u << 24)) : "memory"); return v; }
__device__ __forceinline__ void tma_load_3d_mc(uint32_t dst, const CUtensorMap* map, int c0, int c1, int c2, uint32_t bar) {
    asm volatile("cp.async.bulk.tensor.3d.shared::cluster.global.mbarrier::complete_tx::bytes.multicast::cluster [%0], [%1, {%3, %4, %5}], [%2], %6;"
        :: "r"(dst), "l"(map), "r"(bar), "r"(c0), "r"(c1), "r"(c2), "h"((unsigned short)3) : "memory");
}
__device__ __forceinline__ void bulk_load_mc(uint32_t dst, const void* src, uint32_t bytes, uint32_t bar) {
    asm volatile("cp.async.bulk.shared::cluster.global.mbarrier::complete_tx::bytes.multicast::cluster [%0], [%1], %2, [%3], %4;"
        :: "r"(dst), "l"(src), "r"(bytes), "r"(bar), "h"((unsigned short)3) : "memory");
}
template <int TA> __device__ __forceinline__ void mma_round(float* acc, uint32_t bars, uint32_t a16, uint32_t ph, bool lead, int accum, int it, uint32_t& nw, uint32_t peer, bool lag = false) {
    #pragma unroll
    for (int s = 0; s < RING; s++) {
        if (TA && STAG && s == STAG - 1 && lag) bar_sync_n(TBAR, 256);
        if (TA && STAG && s == STAG && lag) bar_sync_n(TBAR + 1, 256);
        if (!TA && STG1 && s == STG1 && lag) { wgmma_wait<0>(); if (lead) release<(STG1 + RING - 1) % RING>(peer, bars); bar_sync_n(TBAR, 256); }
        mbar_wait_n(FULL(s), ph, nw);
        wgmma_fence();
        #pragma unroll
        for (int k = 0; k < 4; k++) {
            const uint64_t da = TA ? mkd(a16, s * STGB + k * 256, 128, 1024) : mkd(a16, s * STGB + k * 32, 16, 1024, 1);
            const uint64_t db = mkd(SBASE / 16, s * STGB + 16384 + k * 32, 16, 1024, 1);
            if (k == 0 && s == 0) ss128_p<TA, 0>(acc, da, db, accum); else ss128<TA, 0>(acc, da, db);
        }
        wgmma_commit();
        wgmma_wait<1>();

        if ((s == 3 || s == DBGS) && threadIdx.x == 0) DBG_STAMP(32 + it + s);
        if (lead && (s > 0 ? (TA ? accum < 7 : (s != STG1 || !lag)) : accum)) { if (s == 0) release<3>(peer, bars); if (s == 1) release<0>(peer, bars); if (s == 2) release<1>(peer, bars); if (s == 3) release<2>(peer, bars); }
    }
}
__device__ __forceinline__ void gemm_main(float* A, uint32_t sbase, int wg, int warp, int lane, int cb, int tc, int swp) {
    const uint32_t bars = sbase + BAR_OFF;
    const bool lead = tid128() < 2 - REL2;
    const uint32_t a16 = SBASE / 16 + wg * 512;
    uint32_t nw = 0;
    uint32_t peer = bars ^ ((uint32_t)(lane + REL2) << 24);
    asm volatile("" : "+r"(peer));
    asm volatile("barrier.cluster.wait.acquire.aligned;" ::: "memory");
    #pragma unroll 1
    for (int half = 0; half < 2; half++) {
        float2 lam, l16, l32, l64;
        uint32_t a, par;
        unsigned long long* ag;
        #pragma unroll 1
        for (int rd = 0; rd < 4; rd++) mma_round<0>(A, bars, a16, rd & 1, lead, rd, 16 * half + 4 * rd, nw, peer, rd * wg == 3);
        if (STG1 && wg == 0) bar_arrive_n(TBAR, 256);
        {
            mbar_wait_n(EPB, 0, nw);
            const int ln = tid128() & 31, ch = half * 64 + wg * 32 + warp * 8 + (ln >> 2);
            const uint32_t sg = (uint32_t)swp << 31;
            const uint2 p0 = lds64(sbase + LAM_OFF + ch * 16);
            const uint4 p1 = lds128(sbase + LAM_OFF + 2048 + ch * 16);
            par = (lds32(sbase + EPO_OFF) & 1u) | ((ln & 3) == 3 && tc < 15 ? 0u : 2u);
            lam = make_float2(__uint_as_float(p0.x), __uint_as_float(p0.y ^ sg));
            l16 = make_float2(__uint_as_float(p1.x), __uint_as_float(p1.y ^ sg)); l32 = make_float2(__uint_as_float(p1.z), __uint_as_float(p1.w ^ sg));
            l64 = cmul(l32, l32);
            a = sbase + R0 + (((ln >> 3) & 1) ^ swp) * 16384 + (ln >> 4) * 1024 + (wg * 32 + warp * 8 + (ln & 7)) * 16;
            ag = &g_agg[tc * P_DIM + cb * 128 + ch];
        }
        mbar_wait_n(R0F, half, nw);
        wgmma_wait<0>();
        reg_fence<64>(A);
        if (lead) release<RING - 1>(peer, bars);
        #pragma unroll
        for (int r = 1; r < 16; r++) {
            #pragma unroll
            for (int c = 0; c < 2; c++) {
                const float2 v = cfma(lam, make_float2(A[4 * r - 4 + c], A[4 * r - 2 + c]), make_float2(A[4 * r + c], A[4 * r + 2 + c]));
                A[4 * r + c] = v.x; A[4 * r + 2 + c] = v.y;
            }
            if ((r & 1) && r < 12) { const float* u = A + 4 * r - 4; stsm_x4(a + (r >> 1) * 2048, pack2(u[0], u[1]), pack2(u[2], u[3]), pack2(u[4], u[5]), pack2(u[6], u[7])); }
        }
        {
            float2 e = cfma(l16, make_float2(A[60], A[62]), make_float2(A[61], A[63]));
            float2 o = make_float2(__shfl_xor_sync(0xffffffffu, e.x, 1), __shfl_xor_sync(0xffffffffu, e.y, 1));
            stsm_x4(a + 6 * 2048, pack2(A[48], A[49]), pack2(A[50], A[51]), pack2(A[52], A[53]), pack2(A[54], A[55]));
            e = cfma(l32, o, e);
            o = make_float2(__shfl_xor_sync(0xffffffffu, e.x, 2), __shfl_xor_sync(0xffffffffu, e.y, 2));
            stsm_x4(a + 7 * 2048, pack2(A[56], A[57]), pack2(A[58], A[59]), pack2(A[60], A[61]), pack2(A[62], A[63]));
            e = cfma(l64, o, e);
            asm volatile("{\n.reg .pred p;\nsetp.lt.u32 p, %3, 2;\n@p st.relaxed.gpu.global.v2.u32 [%0], {%1, %2};\n}" :: "l"(ag),
                         "r"((__float_as_uint(swp ? e.y : e.x) & ~1u) | par), "r"((__float_as_uint(swp ? e.x : e.y) & ~1u) | par), "r"(par) : "memory");
        }
        bar_arrive_n(DBAR, 384);
        if (threadIdx.x == 0) DBG_STAMP(1 + half);
        if (HOLD >= 0) bar_sync_n(KBAR, 384);
    }
    #pragma unroll 1
    for (int rd = 0; rd < 8; rd++) mma_round<1>(A, bars, a16, rd & 1, lead, rd, 32 + 4 * rd, nw, peer, rd * wg == 7);
}

__device__ __forceinline__ const CUtensorMap* keep(const CUtensorMap* p) { return reinterpret_cast<const CUtensorMap*>(__shfl_sync(0xffffffffu, reinterpret_cast<unsigned long long>(p), 0)); }
__device__ __forceinline__ void produce(const Maps& mp, uint32_t sbase, int RK, int cb, int tc, int db, int rc) {
    const uint32_t bars = sbase + BAR_OFF;
    const CUtensorMap *mb = keep(&mp.BB), *mx = keep(&mp.X), *cr = keep(&mp.Cre), *ci = keep(&mp.Cim);
    if (!elect_one()) return;
    uint32_t nw = 0;
    int kc = 256, row = cb * 16;
    const int xj = tc * 8, xr = RK * 8;
    #pragma unroll 1
    for (int rd = 1; rd < 8; rd++) {
        #pragma unroll
        for (int s = 0; s < RING; s++) {
            mbar_wait_n(EMPTY(s), (rd - 1) & 1, nw);
            mbar_expect_tx(FULL(s), STGB);
            tma_load_4d(sbase + s * STGB, mb, kc, row, FULL(s));
            tma_load_3d_mc(sbase + s * STGB + 16384 + RK * 8192, mx, kc, xj, xr, FULL(s));
            asm volatile("add.s32 %0, %0, 64;" : "+r"(kc));
        }
        if (rd == 3) { kc = 0; row += 8; }
    }
    const uint8_t* hs = reinterpret_cast<const uint8_t*>(g_h) + rc * 32 * 16384 + RK * 8192;
    const int d0 = db * 4, d1 = db * 4 + 32;
    #pragma unroll 1
    for (int rd = 8; rd < 16; rd++) {
        const CUtensorMap* cm = (rd & 2) ? ci : cr;
        kc = (rd & 1) * 512 + (rd & 4) * 16;
        #pragma unroll
        for (int s = 0; s < RING; s++) {
            mbar_wait_n(EMPTY(s), (rd - 1) & 1, nw);
            mbar_expect_tx(FULL(s), STGB);
            tma_load_5d(sbase + s * STGB + 16384, cm, kc, d0, FULL(s));
            tma_load_5d(sbase + s * STGB + 24576, cm, kc, d1, FULL(s));
            if (s == 0) { mbar_wait_n(HOK((rd >> 1) & 3), 0, nw); if (!(rd & 3)) DBG_STAMP(13 + ((rd >> 2) & 1)); }
            bulk_load_mc(sbase + s * STGB + RK * 8192, hs, 8192, FULL(s));
            asm volatile("add.s32 %0, %0, 128;" : "+r"(kc));
            asm volatile("add.s64 %0, %0, 16384;" : "+l"(hs));
        }
    }
}

__global__ void __cluster_dims__(2, 1, 1) __launch_bounds__(640, 1)
fused_kernel(const __grid_constant__ Maps mp, const __nv_bfloat16* __restrict__ x,
             const __nv_bfloat16* __restrict__ w_r, const __nv_bfloat16* __restrict__ w_i,
             const __nv_bfloat16* __restrict__ lam_re, const __nv_bfloat16* __restrict__ lam_im,
             const __nv_bfloat16* __restrict__ log_dt, const __nv_bfloat16* __restrict__ dskip,
             const __nv_bfloat16* __restrict__ gate_w,
             const __nv_bfloat16* __restrict__ Cre, const __nv_bfloat16* __restrict__ Cim,
             const __nv_bfloat16* __restrict__ Bre, const __nv_bfloat16* __restrict__ Bim, float* __restrict__ out, unsigned int full, int swp) {
    extern __shared__ __align__(1024) uint8_t smem[];
    const uint32_t sbase = SBASE + ((blockIdx.x & 1) << 24);
    if (smem_u32(smem) != sbase) __trap();
    const uint32_t bars = sbase + BAR_OFF;
    const int tid = threadIdx.x, lane = tid & 31;
    const int wg = __shfl_sync(0xffffffffu, tid >> 7, 0), warp = __shfl_sync(0xffffffffu, (tid >> 5) & 3, 0);
    if (EPF && blockIdx.x < 128 && tid < 96 * EPF) {
        const int w = tid / 96, i = tid - 96 * w, row = i >> 2;
        const __nv_bfloat16* p = row < 16 ? x + (blockIdx.x * 16 + row) * 1024 : (row < 20 ? Bre : Bim) + ((blockIdx.x >> 4) * 128 + (blockIdx.x & 15) * 4 + (row & 3)) * 1024;
        pf_line(p + (4 * w + (i & 3)) * 64);
    }
    int cta = blockIdx.x;
    {
        unsigned int smid, nsm;
        asm volatile("mov.u32 %0, %%smid;" : "=r"(smid));
        asm volatile("mov.u32 %0, %%nsmid;" : "=r"(nsm));
        if (nsm == full) {
            const int t = smid >> 1, u = (t - 32) / 7;
            const int g = t < 32 ? (t & 7) : (t < 60 ? t - 31 - 7 * u : 0), idx = t < 32 ? (t >> 3) : (t < 60 ? 4 + u : t - 58);
            const int lg = (0x73216540 >> (4 * g)) & 7;
            cta = ((t & ~1) == 60 ? 8 + 2 * t : 16 * lg + 2 * idx) + (TST & 1 ? (blockIdx.x & 1) : (smid & 1));
        }
    }
    const int cb = 2 * (cta >> 5) + (cta & 1), tc = (cta >> 1) & 15;
    const int db = 2 * ((cta >> 4) & 3) + (cta & 1), rc = 8 * ((cta >> 6) & 1) + ((cta >> 1) & 7);
    const long long t_start = clock64();
    if (tid >= 512 && tid < 544 && elect_one()) {
        DBG_STAMP(0); DBG_RAW(98, (cta + 1) * 1000);
        for (int s = 0; s < RING; s++) { mbar_init(FULL(s), 1); mbar_init(EMPTY(s), 4); }
        for (int i = 0; i < 12; i++) mbar_init(XB + 8 * i, i == 4 ? 2 : (i == 2 ? 129 : (i == 5 ? 8 : 1)));
        mbar_init(X1C, 1);
        sts32(sbase + ROLE_OFF, cta); sts32(sbase + SACT_OFF, 0u); sts32(sbase + SACT_OFF + 8, 0u);
        asm volatile("fence.mbarrier_init.release.cluster;" ::: "memory");
        fence_async();
        if (cta < 128) {
            #pragma unroll
            for (int s = 0; s < RING; s++) {
                mbar_expect_tx(FULL(s), STGB);
                tma_load_4d(sbase + s * STGB, &mp.BB, s * 64, cb * 16, FULL(s));
                tma_load_3d(sbase + s * STGB + 16384, &mp.X, s * 64, tc * 8, 0, FULL(s));
                tma_load_3d(sbase + s * STGB + 24576, &mp.X, s * 64, tc * 8, 8, FULL(s));
            }
        }
    }
    __syncthreads();
    asm volatile("barrier.cluster.arrive.relaxed.aligned;" ::: "memory");
    if (wg >= 2 || cta >= 128) asm volatile("barrier.cluster.wait.acquire.aligned;" ::: "memory");
    if (wg == 4) {
        asm volatile("setmaxnreg.dec.sync.aligned.u32 24;");
        if (warp == 0) {
            const int prole = (TST & 4) ? (cta ^ 1) : __shfl_sync(0xffffffffu, peer_role(sbase + ROLE_OFF), 0);
            const uint32_t rk = blockIdx.x & 1;
            if (cta >= 128) bar_arrive_n(DBAR + (prole >> 30), 64);
            const uint8_t* hs = reinterpret_cast<const uint8_t*>(g_h) + rc * 32 * 16384;
            if (cta < 128 && __all_sync(0xffffffffu, prole == (cta ^ 1))) {
                produce(mp, sbase, rk, cb, tc, db, rc);
            } else if (cta < 128) {
                uint32_t nw = 0;
                if (elect_one()) {
                    #pragma unroll 1
                    for (int it = RING; it < 64; it++) {
                        const int s = it % RING;
                        const uint32_t sa = sbase + s * STGB;
                        if (prole >= 128) mbar_arrive2(EMPTY(s));
                        mbar_wait_n(EMPTY(s), ((it / RING) - 1) & 1, nw);
                        mbar_expect_tx(FULL(s), STGB);
                        if (it < 32) {
                            tma_load_4d(sa, &mp.BB, (it & 15) * 64, cb * 16 + (it >> 4) * 8, FULL(s));
                            tma_load_3d(sa + 16384, &mp.X, (it & 15) * 64, tc * 8, 0, FULL(s));
                            tma_load_3d(sa + 24576, &mp.X, (it & 15) * 64, tc * 8, 8, FULL(s));
                        } else {
                            const CUtensorMap* cm = (it & 8) ? &mp.Cim : &mp.Cre;
                            tma_load_5d(sa + 16384, cm, (it & 7) * 128 + (it & 16) * 4, db * 4, FULL(s));
                            tma_load_5d(sa + 24576, cm, (it & 7) * 128 + (it & 16) * 4, db * 4 + 32, FULL(s));
                            mbar_wait_n(HOK((it >> 3) & 3), 0, nw);
                            bulk_load(sa, hs + (it - 32) * 16384, 16384, FULL(s));
                        }
                    }
                }
            } else if (cta >= 128 && prole < 128 && lane == 0) {
                mbar_arrive2(EMPTY(RING - 1));
                #pragma unroll 1
                for (int p = 0; p < 8; p++) mbar_wait(EMPTY(RING - 1), p & 1);
            }
        } else if (warp == 1) {
            if (cta < 130) {
                #pragma unroll 1
                for (int i = lane; i < 128; i += 32) {
                    const int p = (cb & 7) * 128 + i;
                    const float dt = bf16r(expf(__bfloat162float(log_dt[p]))), lr = __bfloat162float(lam_re[p]), li = __bfloat162float(lam_im[p]);
                    const float er = expf(dt * lr), den = lr * lr + li * li;
                    float sn, cs; sincospif(dt * li * 0.31830988618379067154f, &sn, &cs);
                    cs *= er; sn *= er;
                    sts128(sbase + LAM_OFF + i * 16, __float_as_uint(cs), __float_as_uint(sn),
                           __float_as_uint(__fdividef((cs - 1.f) * lr + sn * li, den)), __float_as_uint(__fdividef(sn * lr - (cs - 1.f) * li, den)));
                    float2 l = make_float2(cs, sn);
                    l = cmul(l, l); l = cmul(l, l); l = cmul(l, l); l = cmul(l, l);
                    const float2 l2 = cmul(l, l);
                    sts128(sbase + LAM_OFF + 2048 + i * 16, __float_as_uint(l.x), __float_as_uint(l.y), __float_as_uint(l2.x), __float_as_uint(l2.y));
                }
                __syncwarp();
                if (lane == 0) mbar_arrive(EPB);
                mbar_wait(EPB, 0);
                const unsigned int epoch = lds32(sbase + EPO_OFF);
                const bool one = elect_one();
                if (one) {
                    while (clock64() - t_start < TTAB) { __nanosleep(100); }
                    mbar_expect_tx(X1B, 16384 + 2048 + 10240);
                    bulk_load(sbase + B16F_OFF, g_img.b16f, 2048, X1B);
                    bulk_load(sbase + R2, cta < 2 ? g_img.m4re[cta] : g_img.h[cta & 1].m4, 8192, X1B);
                    bulk_load(sbase + R2 + 8192, g_img.h[cta & 1].b16i, 2048, X1B);
                    if (W0E) { delay(300); load_w(mp.W, sbase, cta, 0); }
                }
                __syncwarp();
                if (cta < 128) bar_sync_n(GBAR, 288);
                if (one) {
                    if (cta < 128) { red_release(&g_cnt1); DBG_STAMP(15); }
                    mbar_expect_tx(X1C, 16384);
                    wait_counter(&g_cnt1, 128u * epoch);
                    DBG_STAMP(8);
                    load_paced(sbase + R1, (ABL & 2) ? reinterpret_cast<const uint8_t*>(x) + (cta & 127) * 32768 : reinterpret_cast<const uint8_t*>(g_X1 + (cta & 127) * 2048), 16384 / PSZ, X1B);
                    load_paced(sbase + R1 + 16384, (ABL & 2) ? reinterpret_cast<const uint8_t*>(x) + (cta & 127) * 32768 + 16384 : reinterpret_cast<const uint8_t*>(g_X1 + (cta & 127) * 2048 + 1024), 16384 / PSZ, X1C);
                }
                #pragma unroll 1
                for (int i = 0; i < 4; i++) {
                    if (one && (i || !W0E)) load_w(mp.W, sbase, cta, i);
                    __syncwarp();
                    if (i != 2) bar_sync_n(LBAR + i, 160);
                    else if (one) mbar_wait(WQ(1), 0);
                }
                if (one) {
                    red_release(cta < 128 ? &g_cnt2 : &g_cnt3);
                    DBG_STAMP(30);
                    if (cta < 128) {
                        const uint8_t* img = (ABL & 2) ? reinterpret_cast<const uint8_t*>(x) + (cta & 63) * 65536 : reinterpret_cast<const uint8_t*>(g_X2) + (8 * rc + db) * X2_IMG;
                        mbar_expect_tx(ZOK, 32768 - 256);
                        wait_counter(&g_cnt2, 128u * epoch);
                        DBG_STAMP(31);
                        bulk_load(sbase + R1 + 1152, img + 1152, 15232, ZOK);
                        bulk_load(sbase + R1 + 16384 + 1152, img + X2_IMG / 2 + 1152, 15232, ZOK);
                        bulk_load(sbase + R1, img, 1024, ZOK);
                        bulk_load(sbase + R1 + 16384, img + X2_IMG / 2, 1024, ZOK);
                    }
                }
            }
        } else if (warp == 2) {
            if (cta < 128) {
                const uint8_t* bp = reinterpret_cast<const uint8_t*>((lane & 16) ? Bim : Bre) + (cb * 128 + tc * 4 + ((lane >> 2) & 3)) * 2048 + (lane & 3) * 128;
                asm volatile("prefetch.tensormap [%0];" :: "l"(&mp.Xr) : "memory");
                while (clock64() - t_start < TXT) { }
                if (elect_one()) {
                    mbar_expect_tx(XB, 32768 + 256);
                    bulk_load(sbase + GATE_OFF, gate_w + db * 64, 128, XB);
                    bulk_load(sbase + GATE_OFF + 128, gate_w + db * 64 + 512, 128, XB);
                    #pragma unroll
                    for (int i = 0; i < 8; i++) tma_load_2d(sbase + R0 + i * 4096, &mp.Xr, rc * 1024 + db * 64 + (i >> 2) * 512, (i & 3) * 32, XB);
                }
                __syncwarp();
                pf_line(bp + 1024); pf_line(bp + 1536);
                if ((cta & 63) < 12) pf_line(reinterpret_cast<const uint8_t*>(&g_img) + (cta & 63) * 4096 + lane * 128);
                while (clock64() - t_start < PFW) { }
                const uint32_t wrow = (((cta & 1) ? 128 - (cta >> 1) : (cta >> 1)) + 128 * (lane >> 1)) & 2047;
                const uint8_t* wp = reinterpret_cast<const uint8_t*>(lane & 1 ? w_i : w_r) + wrow * 1026u;

                #pragma unroll 1
                for (int k = 0; k < ((ABL & 4) ? 0 : 9); k++) { pf_line(wp + (k < 8 ? k * 128 : 1024)); __nanosleep(200); }
                while (clock64() - t_start < PFB) { }
                #pragma unroll 1
                for (int k = 0; k < 16; k += 4) { pf_line(bp + 64 * 2048 + k * 128); __nanosleep(200); }
                const uint8_t* cp = reinterpret_cast<const uint8_t*>((lane & 16) ? Cim : Cre) + (cta * 8 + (lane & 7)) * 2048 + (lane & 8) * 32;
                #pragma unroll 1
                for (int k = 0; k < 8; k++) {
                    while (clock64() - t_start < PFC + k * PFCS) { __nanosleep(100); }
                    pf_line(cp + (k & 3) * 512 + (k >> 2) * 128);
                }
            }
        } else {
            unsigned int epoch = 0;
            if (cta >= 128) bar_sync_n(DBAR, 64);
            if (lane == 0) {
                epoch = atomicAdd(&g_ticket, 1u);
                epoch = (full ? epoch / NCTA : epoch / 130u) + 1u;
                sts32(sbase + EPO_OFF, epoch);
                mbar_arrive(EPB);
            }
            __syncwarp();
            if (cta < 128) {
                #pragma unroll 1
                for (int i = 0; i < 4; i++) {
                    bar_sync_n(HBAR + i, 160);
                    if (lane == 0) {
                        red_release(&g_cnth(i));
                        if (!(i & 1)) DBG_STAMP(4 + (i >> 1));
                        wait_counter(&g_cnth(i), 128u * epoch);
                        mbar_arrive(HOK(i));
                    }
                    __syncwarp();
                }
                if (lane == 0) {
                    mbar_expect_tx(XB, 32768);
                    #pragma unroll 1
                    for (int i = 0; i < 8; i++) { tma_load_2d(sbase + R0 + i * 4096, &mp.Xr, rc * 1024 + db * 64 + (i >> 2) * 512, (i & 3) * 32, XB); __nanosleep(XRS); }
                }
            } else if (cta >= 130 && lane == 0) {
                #pragma unroll 1
                for (int i = 0; i < (1 << 22); i++) {
                    __nanosleep(200);
                    if ((int)(*reinterpret_cast<volatile unsigned int*>(&g_ticket) - NCTA * epoch) >= 0) break;
                }
            }
        }
    } else if (wg >= 2) {
      if (cta < 128) {
          float2 w1, w32;
          sincospif((float)(16 * tid128() + rc) * (1.f / 1024.f), &w1.y, &w1.x);
          w32 = cmul(w1, w1); w32 = cmul(w32, w32); w32 = cmul(w32, w32); w32 = cmul(w32, w32); w32 = cmul(w32, w32);
          gen_dft(sbase + R1, tid128(), w1, wg == 2 ? make_float2(1.f, 0.f) : make_float2(w32.x, -w32.y), 4 * wg - 8, 4 * wg - 4, 0.5f);
          fence_async();
          bar_sync_n(wg, 128);
          mbar_wait(XB, 0);
          if (tid == 256) DBG_STAMP(9);
          fft_p1(sbase, wg - 2, rc, db, (uint32_t)t_start + P1END);
          bar_arrive_n(GBAR, 288);
      }
      if (wg == 3) {
        asm volatile("setmaxnreg.inc.sync.aligned.u32 120;");
        if (cta < 128) {
            if (cta < 128) {
                mbar_wait(EPB, 0);
                #pragma unroll 1
                for (int half = 0; half < 2; half++) {
                    const int t1 = tid128(), ch = t1 >> 1, hf = t1 & 1, p = cb * 128 + half * 64 + ch;
                    if (half) {
                        mbar_wait(X1B, 0);
                        float s = 0.f;
                        #pragma unroll
                        for (int i = 0; i < 16; i++) s += __ldcg(&g_gp[(16 * rc + i) * 128 + t1]);
                        const float gv = bf16r(__fdividef(1.f, 1.f + expf(-bf16r(s))));
                        sts32(sbase + GATE_OFF + 4 * t1, pack2(gv, 1.f - gv));
                    }
                    const uint4 pm = lds128(sbase + LAM_OFF + (half * 64 + ch) * 16);
                    float2 lam = make_float2(__uint_as_float(pm.x), __uint_as_float(pm.y));
                    float cr = __uint_as_float(pm.z), ci = __uint_as_float(pm.w);
                    const uint4 pp = lds128(sbase + LAM_OFF + 2048 + (half * 64 + ch) * 16);
                    const float2 l16 = make_float2(__uint_as_float(pp.x), __uint_as_float(pp.y)), l32 = make_float2(__uint_as_float(pp.z), __uint_as_float(pp.w));
                    const float2 l64 = cmul(l32, l32), l128 = cmul(l64, l64), l256 = cmul(l128, l128);
                    const unsigned int par = lds32(sbase + EPO_OFF) & 1u;
                    if (__float_as_uint(l256.x) == 0x9e3779b9u) sts32(sbase + SACT_OFF + 4, 0u);
                    bar_sync_n(DBAR, 384);
                    if (t1 == 0) DBG_STAMP(21 + 4 * half);
                    uint2 ur[16], ui[16];
                    #pragma unroll
                    for (int r = 15; r >= 0; r--) { ur[r] = lds64(sbase + R0 + r * 1024 + t1 * 8); ui[r] = lds64(sbase + R0 + 16384 + r * 1024 + t1 * 8); }
                    if (HOLD >= 0) { if (cta > 999) sts32(sbase + SACT_OFF + 4, ui[0].y); bar_arrive_n(KBAR, 384); boundary(); }
                    float2 e[4], E0;
                    e[0] = make_float2(bflo(ur[15].x), bflo(ui[15].x));
                    e[1] = cfma(l16, e[0], make_float2(bfhi(ur[15].x), bfhi(ui[15].x)));
                    e[2] = cfma(l16, e[1], make_float2(bflo(ur[15].y), bflo(ui[15].y)));
                    e[3] = cfma(l16, e[2], make_float2(bfhi(ur[15].y), bfhi(ui[15].y)));
                    E0.x = __shfl_xor_sync(0xffffffffu, e[3].x, 1); E0.y = __shfl_xor_sync(0xffffffffu, e[3].y, 1);
                    const uint2* src = reinterpret_cast<const uint2*>(g_agg) + (tc - 1 - hf) * P_DIM + p;
                    const int nv = tc - hf;
                    uint2 v[8];
                    {
                        const bf2 c2 = asbf2(pack2(cr, cr)), n2 = asbf2(pack2(-cr, -cr)), s2 = asbf2(pack2(-ci, -ci));
                        #pragma unroll
                        for (int r = 15; r >= 0; r--) {
                            if (r == EAGG) {
                                boundary();
                                #pragma unroll
                                for (int i = 0; i < 8; i++) {
                                    v[i] = make_uint2(par, par);
                                    if (2 * i < nv) asm volatile("ld.relaxed.gpu.global.v2.u32 {%0, %1}, [%2];" : "=r"(v[i].x), "=r"(v[i].y) : "l"(src - i * 2 * P_DIM) : "memory");
                                }
                                #pragma unroll
                                for (int q = r; q >= 0; q--) asm volatile("" : "+r"(ur[q].x), "+r"(ur[q].y), "+r"(ui[q].x), "+r"(ui[q].y) :: "memory");
                            }
                            const bf2 a = asbf2(ur[r].x), b = asbf2(ui[r].x), c = asbf2(ur[r].y), d = asbf2(ui[r].y);
                            ur[r].x = asu32(__hfma2(c2, a, __hmul2(s2, b))); ui[r].x = asu32(__hfma2(n2, b, __hmul2(s2, a)));
                            ur[r].y = asu32(__hfma2(c2, c, __hmul2(s2, d))); ui[r].y = asu32(__hfma2(n2, d, __hmul2(s2, c)));
                            asm volatile("" : "+r"(ur[r].x), "+r"(ur[r].y), "+r"(ui[r].x), "+r"(ui[r].y) :: "memory");
                        }
                    }
                    __syncwarp();
                    if (lane == 0) mbar_arrive2(R0F);
                    if (t1 == 0) DBG_STAMP(22 + 4 * half);
                    #pragma unroll 1
                    for (int spins = 0; spins < (1 << 20); spins++) {
                        uint32_t bad = 0;
                        #pragma unroll
                        for (int i = 0; i < 8; i++) bad |= (v[i].x ^ par) | (v[i].y ^ par);
                        if (!__any_sync(0xffffffffu, bad & 1u)) break;
                        #pragma unroll
                        for (int i = 0; i < 8; i++)
                            if (2 * i < nv) asm volatile("ld.relaxed.gpu.global.v2.u32 {%0, %1}, [%2];" : "+r"(v[i].x), "+r"(v[i].y) : "l"(src - i * 2 * P_DIM) : "memory");
                    }
                    if (t1 == 0) { sts32(sbase + SACT_OFF, YIELD); DBG_STAMP(23 + 4 * half); }
                    float2 H = make_float2(__uint_as_float(v[7].x), __uint_as_float(v[7].y));
                    #pragma unroll
                    for (int i = 6; i >= 0; i--) H = cfma(l256, H, make_float2(__uint_as_float(v[i].x), __uint_as_float(v[i].y)));
                    if (hf) H = cmul(H, l128);
                    H.x += __shfl_xor_sync(0xffffffffu, H.x, 1); H.y += __shfl_xor_sync(0xffffffffu, H.y, 1);
                    float2 st[4];
                    st[0] = hf ? cfma(l64, H, E0) : H;
                    st[1] = cfma(l16, st[0], e[0]); st[2] = cfma(l32, st[0], e[1]); st[3] = cfma(l16, cmul(l32, st[0]), e[2]);
                    const bf2 gr0 = asbf2(pack2(cr * st[0].x - ci * st[0].y, cr * st[1].x - ci * st[1].y)), gr1 = asbf2(pack2(cr * st[2].x - ci * st[2].y, cr * st[3].x - ci * st[3].y));
                    const bf2 gi0 = asbf2(pack2(-ci * st[0].x - cr * st[0].y, -ci * st[1].x - cr * st[1].y)), gi1 = asbf2(pack2(-ci * st[2].x - cr * st[2].y, -ci * st[3].x - cr * st[3].y));
                    uint2* dst = reinterpret_cast<uint2*>(g_h + (half * 16 + cb) * 1024 + tc * 64) + t1;
                    lam.y = -lam.y;
                    float2 z = lam;
                    uint32_t pw[16], tp = clk32() + warp * (PCH / 2);
                    #pragma unroll
                    for (int r = 0; r < 16; r++) {
                        pw[r] = pack2(z.x, z.y); z = cmul(z, lam);
                        const bf2 pr = __low2bfloat162(asbf2(pw[r])), pi = __high2bfloat162(asbf2(pw[r]));
                        if (!(r & 1)) pace(tp, 2 * PCR);
                        __stcg(dst + r * 65536, make_uint2(asu32(__hfma2(pr, gr0, __hfma2(pi, neg2(gi0), asbf2(ur[r].x)))), asu32(__hfma2(pr, gr1, __hfma2(pi, neg2(gi1), asbf2(ur[r].y))))));
                    }
                    bar_arrive_n(HBAR + 2 * half, 160);
                    if (t1 == 0) DBG_STAMP(24 + 4 * half);
                    if (PCR == 0) tp = clk32();
                    tp += PCG;
                    #pragma unroll
                    for (int r = 0; r < 16; r++) {
                        const bf2 pr = __low2bfloat162(asbf2(pw[r])), pi = __high2bfloat162(asbf2(pw[r]));
                        if (!(r & 1)) pace(tp, 2 * PCH);
                        __stcg(dst + r * 65536 + 16384, make_uint2(asu32(__hfma2(pr, gi0, __hfma2(pi, gr0, asbf2(ui[r].x)))), asu32(__hfma2(pr, gi1, __hfma2(pi, gr1, asbf2(ui[r].y))))));
                    }
                    bar_arrive_n(HBAR + 2 * half + 1, 160);
                    if (t1 == 0) sts32(sbase + SACT_OFF, 0u);
                }
            }
        }
      } else {
        asm volatile("setmaxnreg.inc.sync.aligned.u32 144;");
        if (cta < 130) {
            if (tid128() == 0) DBG_STAMP(16);
            fft_p2(sbase, bars, cta, w_r, w_i);
            bar_sync_n(LBAR + 3, 160);
            if (tid128() == 0) DBG_STAMP(29);
            if (cta < 128) {
                const int j = tid128();
                if (j < 16) {
                    const uint2 d0 = __ldg(reinterpret_cast<const uint2*>(dskip) + db * 16 + j), d1 = __ldg(reinterpret_cast<const uint2*>(dskip) + db * 16 + 128 + j);
                    sts128(sbase + DSK_OFF + j * 16, d0.x, d0.y, d1.x, d1.y);
                }
                mbar_wait(HOK(2), 0);
                const float gv = bflo(lds32(sbase + GATE_OFF + 4 * j));
                gen_dft(sbase + R2, j, cis(16 * j + rc), make_float2(gv * (1.f / 1048576.f), 0.f), 0, 8, gv * (1.f / 1048576.f));
                const uint8_t* img = reinterpret_cast<const uint8_t*>(g_X2) + (8 * rc + db) * X2_IMG;
                if ((j >> 4) == 4) {
                    wait_counter(&g_cnt3, 2u * lds32(sbase + EPO_OFF));
                    const float cs = g_img.cs[0][4 * rc][0], sn = g_img.cs[0][4 * rc][1];
                    const uint4* s4 = reinterpret_cast<const uint4*>(img + ((j >> 3) & 1) * (X2_IMG / 2) + 16384) + (j & 7);
                    const uint4 a = __ldcg(s4), b = __ldcg(s4 + 64);
                    sts128(sbase + R1 + ((j >> 3) & 1) * 16384 + 1024 + (j & 7) * 16,
                           pack2(cs * bflo(a.x) - sn * bflo(b.x), cs * bfhi(a.x) - sn * bfhi(b.x)), pack2(cs * bflo(a.y) - sn * bflo(b.y), cs * bfhi(a.y) - sn * bfhi(b.y)),
                           pack2(cs * bflo(a.z) - sn * bflo(b.z), cs * bfhi(a.z) - sn * bfhi(b.z)), pack2(cs * bflo(a.w) - sn * bflo(b.w), cs * bfhi(a.w) - sn * bfhi(b.w)));
                }
                fence_async();
                mbar_arrive(ZOK);
            }
        }
      }
    } else {
        if (cta < 128) {
            {
                const int w8 = tid >> 5;
                if (w8 == 0) pf_line(((lane & 16) ? Bim : Bre) + (cb * 128 + tc * 4 + ((lane >> 2) & 3)) * 1024 + (4 + (lane & 3)) * 64);
                else if (w8 < NPF) pf_line(x + (cta * 16 + (lane >> 1)) * 1024 + (2 + 2 * w8 + (lane & 1)) * 64);
            }
            float A[64];
            #pragma unroll
            for (int i = 0; i < 64; i++) A[i] = 0.f;
            gemm_main(A, sbase, wg, warp, lane, cb, tc, swp);
            if (tid == 0) DBG_STAMP(12);
            const int ln = tid128() & 31, row = 64 * wg + 16 * warp + (ln >> 2);
            if (STAG && wg == 0) bar_arrive_n(TBAR, 256);
            mbar_wait(ZOK, 0);
            if (tid == 0) DBG_STAMP(11);
            float om[2];
            om[0] = bfhi(lds32(sbase + GATE_OFF + 4 * row)); om[1] = bfhi(lds32(sbase + GATE_OFF + 4 * row + 32));
            wgmma_wait<0>();
            reg_fence<64>(A);
            #pragma unroll
            for (int i = 0; i < 32; i++) { const float o = om[(i >> 1) & 1], t = o * A[i], u = A[i + 32]; A[i] = fmaf(o, u, t); A[i + 32] = fmaf(-o, u, t); }
            const uint32_t s16 = to16(sbase);
            wgmma_fence();
            #pragma unroll
            for (int ks = 0; ks < 8; ks++)
                ss128<0, 1>(A, mkd(s16 + wg * 512, R2 + (ks >> 2) * 16384 + (ks & 3) * 32, 16, 1024, 1), mkd(s16, R1 + ks * 2048, 16384, 1024, 1));
            wgmma_commit();
            if (STAG && wg == 0) bar_arrive_n(TBAR + 1, 256);
            float* o = out + (size_t)(16 * row + rc) * 1024 + db * 64 + 4 * (ln & 3);
            mbar_wait(XB, 1);
            wgmma_wait<0>();
            reg_fence<64>(A);
            if (tid128() == 0) DBG_STAMP(120 + wg);
            #pragma unroll
            for (int J = 0; J < 4; J++) {
                if (J) boundary();
                const uint4 dk = lds128(sbase + DSK_OFF + (4 * J + (ln & 3)) * 16);
                #pragma unroll
                for (int h = 0; h < 2; h++) {
                    const uint32_t xo = sbase + R0 + (row + 8 * h) * 128 + (ln & 1) * 8 + (((2 * J + ((ln >> 1) & 1)) ^ (ln >> 2)) << 4);
                    uint2 p = lds64(xo), s = lds64(xo + 16384);
                    p.x = hmul2bf(p.x, dk.x); p.y = hmul2bf(p.y, dk.y); s.x = hmul2bf(s.x, dk.z); s.y = hmul2bf(s.y, dk.w);
                    const float* a = A + 8 * J + 2 * h;
                    __stcs(reinterpret_cast<float4*>(o + h * 131072 + J * 16),
                           make_float4(fmaf(om[h], bflo(p.x), a[0] + a[32]), fmaf(om[h], bfhi(p.x), a[1] + a[33]), fmaf(om[h], bflo(p.y), a[4] + a[36]), fmaf(om[h], bfhi(p.y), a[5] + a[37])));
                    __stcs(reinterpret_cast<float4*>(o + h * 131072 + J * 16 + 512),
                           make_float4(fmaf(om[h], bflo(s.x), a[0] - a[32]), fmaf(om[h], bfhi(s.x), a[1] - a[33]), fmaf(om[h], bflo(s.y), a[4] - a[36]), fmaf(om[h], bfhi(s.y), a[5] - a[37])));
                }
            }
            if (tid == 128) { DBG_STAMP(122); DBG_END; }
            if (tid == 0) DBG_STAMP(7);
        }
    }
}

typedef CUresult (*PFN_encodeTiled_t)(CUtensorMap*, CUtensorMapDataType, cuuint32_t, void*, const cuuint64_t*, const cuuint64_t*,
                                      const cuuint32_t*, const cuuint32_t*, CUtensorMapInterleave, CUtensorMapSwizzle,
                                      CUtensorMapL2promotion, CUtensorMapFloatOOBfill);

static CUresult make_map(PFN_encodeTiled_t enc, CUtensorMap* m, int rank, const void* ptr, const cuuint64_t* dims, const cuuint64_t* strides, const cuuint32_t* box) {
    cuuint32_t es[5] = {1, 1, 1, 1, 1};
    return enc(m, CU_TENSOR_MAP_DATA_TYPE_BFLOAT16, rank, (void*)ptr, dims, strides, box, es, CU_TENSOR_MAP_INTERLEAVE_NONE, CU_TENSOR_MAP_SWIZZLE_128B,
        CU_TENSOR_MAP_L2_PROMOTION_L2_128B, CU_TENSOR_MAP_FLOAT_OOB_FILL_NONE);
}
static void make_map_2d(PFN_encodeTiled_t enc, CUtensorMap* m, const void* ptr, int rows, int cols, int box_rows) {
    cuuint64_t dims[2] = {(cuuint64_t)cols, (cuuint64_t)rows};
    cuuint64_t strides[1] = {(cuuint64_t)cols * 2};
    cuuint32_t box[2] = {64, (cuuint32_t)box_rows};
    make_map(enc, m, 2, ptr, dims, strides, box);
}

extern "C" void kernel_launch(void* const* d_in, const int* in_sizes, int n_in, void* d_out, int out_size) {
    const __nv_bfloat16* x = (const __nv_bfloat16*)d_in[0];
    const __nv_bfloat16* w_r = (const __nv_bfloat16*)d_in[1];
    const __nv_bfloat16* w_i = (const __nv_bfloat16*)d_in[2];
    const __nv_bfloat16* lam_re = (const __nv_bfloat16*)d_in[4];
    const __nv_bfloat16* lam_im = (const __nv_bfloat16*)d_in[5];
    const __nv_bfloat16* B_re = (const __nv_bfloat16*)d_in[6];
    const __nv_bfloat16* B_im = (const __nv_bfloat16*)d_in[7];
    const __nv_bfloat16* C_re = (const __nv_bfloat16*)d_in[8];
    const __nv_bfloat16* C_im = (const __nv_bfloat16*)d_in[9];
    const __nv_bfloat16* log_dt = (const __nv_bfloat16*)d_in[10];
    const __nv_bfloat16* dskip = (const __nv_bfloat16*)d_in[11];
    const __nv_bfloat16* gate_w = (const __nv_bfloat16*)d_in[12];

    static PFN_encodeTiled_t enc = nullptr;
    static Maps mp;
    static int grid = 130, swp = 0, copyB = 0;
    static void* bcopy = nullptr;
    static const void* key[7] = {nullptr, nullptr, nullptr, nullptr, nullptr, nullptr, nullptr};
    if (!enc) {
        cudaDriverEntryPointQueryResult qres;
        cudaGetDriverEntryPoint("cuTensorMapEncodeTiled", (void**)&enc, cudaEnableDefault, &qres);
        cudaFuncSetAttribute(fused_kernel, cudaFuncAttributeMaxDynamicSharedMemorySize, TOT_SMEM);
        int dev = 0, nsm = 0;
        cudaGetDevice(&dev);
        cudaDeviceGetAttribute(&nsm, cudaDevAttrMultiProcessorCount, dev);
        grid = nsm == NCTA ? NCTA : 130;
    }
    if (key[0] != x || key[1] != B_re || key[2] != B_im || key[3] != C_re || key[4] != C_im || key[5] != w_r || key[6] != w_i) {
        cudaGetSymbolAddress(&bcopy, g_Bcopy);
        {
            const uintptr_t a = (uintptr_t)B_re, b = (uintptr_t)B_im;
            swp = b < a;
            cuuint64_t dims[4] = {D_DIM, 8, 2, P_DIM / 8};
            cuuint64_t strides[3] = {D_DIM * 2, (cuuint64_t)(swp ? a - b : b - a), D_DIM * 2 * 8};
            cuuint32_t box[4] = {64, 8, 2, 8};
            copyB = strides[1] == 0 || (strides[1] & 15) || strides[1] >= (1ull << 39);
            if (!copyB) copyB = make_map(enc, &mp.BB, 4, swp ? B_im : B_re, dims, strides, box) != CUDA_SUCCESS;
            if (copyB) {
                swp = 0; strides[1] = (cuuint64_t)P_DIM * D_DIM * 2;
                make_map(enc, &mp.BB, 4, bcopy, dims, strides, box);
            }
        }
        {
            cuuint64_t dims[3] = {D_DIM, S_LEN / 16, 16};
            cuuint64_t strides[2] = {D_DIM * 2 * 16, D_DIM * 2};
            cuuint32_t box[3] = {64, 8, 8};
            make_map(enc, &mp.X, 3, x, dims, strides, box);
        }
        make_map_2d(enc, &mp.Xr, x, S_LEN / 16, D_DIM * 16, 32);
        {
            cuuint64_t dims[5] = {P_DIM, 2, 4, 2, D_DIM / 16};
            cuuint64_t strides[4] = {P_DIM * 2, P_DIM * 2 * 4, P_DIM * 2 * 2, P_DIM * 2 * 16};
            cuuint32_t box[5] = {64, 2, 4, 2, 4};
            make_map(enc, &mp.Cre, 5, C_re, dims, strides, box);
            make_map(enc, &mp.Cim, 5, C_im, dims, strides, box);
        }
        for (int a = 0; a < 2; a++) {
            cuuint64_t dims[3] = {128 * 513 - 448, 8, 16};
            cuuint64_t strides[2] = {128, 128 * 513 * 2};
            cuuint32_t box[3] = {64, 8, 4}, es[3] = {1, 1, 1};
            enc(&mp.W[a], CU_TENSOR_MAP_DATA_TYPE_BFLOAT16, 3, (void*)(a ? w_i : w_r), dims, strides, box, es, CU_TENSOR_MAP_INTERLEAVE_NONE, CU_TENSOR_MAP_SWIZZLE_128B,
                CU_TENSOR_MAP_L2_PROMOTION_L2_128B, CU_TENSOR_MAP_FLOAT_OOB_FILL_NONE);
        }
        key[5] = w_r; key[6] = w_i;
        key[0] = x; key[1] = B_re; key[2] = B_im; key[3] = C_re; key[4] = C_im;
    }
    if (copyB) {
        cudaMemcpyAsync(bcopy, B_re, (size_t)P_DIM * D_DIM * 2, cudaMemcpyDeviceToDevice, cudaStreamPerThread);
        cudaMemcpyAsync((char*)bcopy + (size_t)P_DIM * D_DIM * 2, B_im, (size_t)P_DIM * D_DIM * 2, cudaMemcpyDeviceToDevice, cudaStreamPerThread);
    }
    fused_kernel<<<grid, 640, TOT_SMEM, cudaStreamPerThread>>>(mp, x, w_r, w_i, lam_re, lam_im, log_dt, dskip, gate_w, C_re, C_im, B_re, B_im,
        (float*)d_out, grid == NCTA ? NCTA : 0u, swp);
}
```

```cpp
#include <cuda_runtime.h>
#include <cuda_bf16.h>
#include <cuda.h>
#include <stdint.h>

#define S_LEN 2048
#define D_DIM 1024
#define P_DIM 1024

namespace ct {
constexpr double PI = 3.14159265358979323846264338327950288;
constexpr double tsin(double x) { double term = x, sum = x; for (int i = 1; i < 12; i++) { term *= -x * x / ((2 * i) * (2 * i + 1)); sum += term; } return sum; }
constexpr double tcos(double x) { double term = 1, sum = 1; for (int i = 1; i < 12; i++) { term *= -x * x / ((2 * i - 1) * (2 * i)); sum += term; } return sum; }
struct CosTab { double v[513]; };
constexpr CosTab make_cos() {
    CosTab t{};
    for (int m = 0; m <= 512; m++) t.v[m] = m == 512 ? 0.0 : (m <= 256 ? tcos(2 * PI * m / 2048.0) : tsin(2 * PI * (512 - m) / 2048.0));
    return t;
}
constexpr CosTab COS = make_cos();
constexpr double cos2048(int m) {
    m &= 2047;
    if (m > 1024) m = 2048 - m;
    if (m > 512) return -COS.v[1024 - m];
    return COS.v[m];
}
constexpr double sin2048(int m) { return cos2048(m - 512); }
constexpr unsigned short bf16bits(double v) {
    if (v == 0.0) return 0;
    unsigned short s = 0;
    if (v < 0) { s = 0x8000; v = -v; }
    int e = 0;
    while (v >= 2.0) { v *= 0.5; e++; }
    while (v < 1.0) { v *= 2.0; e--; }
    double r = v * 128.0;
    int ri = (int)r;
    double fr = r - ri;
    if (fr > 0.5 || (fr == 0.5 && (ri & 1))) ri++;
    if (ri == 256) { ri = 128; e++; }
    return (unsigned short)(s | ((e + 127) << 7) | (ri - 128));
}
constexpr int kmaj(int row, int k, int sbo) { return ((row >> 3) * sbo + (k >> 3) * 128 + (row & 7) * 16 + (k & 7) * 2) >> 1; }
constexpr double rot(int ro, int ri, int a) { return ro == ri ? cos2048(a) : (ro == 0 ? sin2048(a) : -sin2048(a)); }
constexpr int bin(int n) { return (n & 8) | ((n & 3) << 1) | ((n >> 2) & 1); }
constexpr int bout(int n) { return ((n & 2) << 2) | ((n >> 1) & 6) | (n & 1); }
struct Half {
    unsigned short m4[4096];
    unsigned short b16i[1024];
    unsigned short tw[2][128][8];
};
struct Img { unsigned short b16f[1024]; Half h[2]; float cs[16][128][2]; unsigned short m4re[2][4096]; };
constexpr Img make_img() {
    Img t{};
    for (int n = 0; n < 32; n++) for (int k = 0; k < 32; k++) t.b16f[kmaj(n, k, 512)] = bf16bits(rot(((n >> 4) ^ (n >> 3)) & 1, k >> 4, bin(k & 15) * (n & 15) * 128));
    for (int r = 0; r < 16; r++) for (int j = 0; j < 128; j++) { t.cs[r][j][0] = (float)cos2048(16 * j + r); t.cs[r][j][1] = (float)sin2048(16 * j + r); }
    for (int ke = 0; ke < 2; ke++) {
        Half& h = t.h[ke];
        for (int n = 0; n < 32; n++) for (int k = 0; k < 32; k++) h.b16i[kmaj(n, k, 512)] = bf16bits(rot(n >> 4, ((k >> 4) ^ (k >> 3)) & 1, -bout(n & 15) * (k & 15) * 128));
        for (int m = 0; m < 64; m++) for (int k = 0; k < 64; k++) {
            int a = 4 * (m >> 3) + (m & 3), ro = (m >> 2) & 1, kx = 8 * (k >> 4) + (k & 7), ri = (k >> 3) & 1;
            h.m4[kmaj(m, k, 1024)] = bf16bits(rot(ro, ri, -a * (ke + 2 * kx) * 32));
            t.m4re[ke][kmaj(m, k, 1024)] = ro ? 0 : h.m4[kmaj(m, k, 1024)];
        }
        for (int tid = 0; tid < 128; tid++) {
            int kap = ke + 2 * (tid >> 2), q = tid & 3;
            for (int hb = 0; hb < 2; hb++) for (int e = 0; e < 2; e++) {
                int n = 8 * hb + 2 * q + e;
                h.tw[0][tid][4 * hb + e] = bf16bits(cos2048(2 * bin(n) * kap));  h.tw[0][tid][4 * hb + 2 + e] = bf16bits(-sin2048(2 * bin(n) * kap));
                h.tw[1][tid][4 * hb + e] = bf16bits(cos2048(2 * bout(n) * kap)); h.tw[1][tid][4 * hb + 2 + e] = bf16bits(sin2048(2 * bout(n) * kap));
            }
        }
    }
    return t;
}
}
__device__ __align__(128) const ct::Img g_img = ct::make_img();

#define SBASE 0x400u
#define RING 4
#define STGB 32768
#define R0 (4 * 32768)
#define R1 (5 * 32768)
#define R2 (6 * 32768)
#define B16F_OFF (7 * 32768)
#define BAR_OFF (B16F_OFF + 2048)
#define GATE_OFF (BAR_OFF + 256)
#define DSK_OFF (GATE_OFF + 512)
#define TOT_SMEM (DSK_OFF + 256)
#define NCTA 132
#define X2_IMG 36864

__device__ __align__(1024) uint4 g_X1[128 * 2048];
__device__ __align__(1024) uint4 g_X2[128 * X2_IMG / 16];
__device__ __align__(128) float g_gp[256 * 128];
__device__ __align__(1024) uint4 g_h[16 * 32 * 1024];
__device__ __align__(128) unsigned long long g_agg[16 * P_DIM];
__device__ __align__(128) unsigned int g_cnt[8 * 32];
__device__ __align__(1024) __nv_bfloat16 g_Bcopy[2 * P_DIM * D_DIM];
#define g_ticket g_cnt[0]
#define g_cnt1 g_cnt[32]
#define g_cnt2 g_cnt[64]
#define g_cnt3 g_cnt[224]
#define g_cnth(i) g_cnt[96 + 32 * (i)]


__device__ __forceinline__ float bf16r(float v) { return __bfloat162float(__float2bfloat16_rn(v)); }
__device__ __forceinline__ float2 cmul(float2 a, float2 b) { return make_float2(a.x * b.x - a.y * b.y, a.x * b.y + a.y * b.x); }
__device__ __forceinline__ float2 cfma(float2 a, float2 b, float2 c) {
    float re = fmaf(a.x, b.x, c.x); re = fmaf(-a.y, b.y, re);
    float im = fmaf(a.x, b.y, c.y); im = fmaf(a.y, b.x, im);
    return make_float2(re, im);
}
__device__ __forceinline__ uint32_t smem_u32(const void* p) { return (uint32_t)__cvta_generic_to_shared(p); }
__device__ __forceinline__ void bar_sync_n(int id, int n) { asm volatile("bar.sync %0, %1;" :: "r"(id), "r"(n) : "memory"); }
__device__ __forceinline__ void bar_arrive_n(int id, int n) { asm volatile("bar.arrive %0, %1;" :: "r"(id), "r"(n) : "memory"); }
__device__ __forceinline__ uint32_t pack2(float lo, float hi) { uint32_t r; asm("cvt.rn.bf16x2.f32 %0, %1, %2;" : "=r"(r) : "f"(hi), "f"(lo)); return r; }
__device__ __forceinline__ uint64_t mkd(uint32_t b16, uint32_t off, uint32_t lbo, uint32_t sbo, uint32_t swz = 0) {
    uint64_t d;
    asm("mov.b64 %0, {%1, %2};" : "=l"(d) : "r"(b16 + ((off >> 4) + ((lbo >> 4) << 16))), "r"((sbo >> 4) | (swz << 30)));
    return d;
}
__device__ __forceinline__ void wgmma_fence() { asm volatile("wgmma.fence.sync.aligned;" ::: "memory"); }
__device__ __forceinline__ void wgmma_commit() { asm volatile("wgmma.commit_group.sync.aligned;" ::: "memory"); }
template <int N> __device__ __forceinline__ void wgmma_wait() { asm volatile("wgmma.wait_group.sync.aligned %0;" :: "n"(N) : "memory"); }
__device__ __forceinline__ void fence_async() { asm volatile("fence.proxy.async.shared::cta;" ::: "memory"); }
template <int N> __device__ __forceinline__ void reg_fence(float* d) {
    #pragma unroll
    for (int i = 0; i < N; i++) asm volatile("" : "+f"(d[i]) :: "memory");
}
#define X16(c, d, o) c(d[o]),c(d[o+1]),c(d[o+2]),c(d[o+3]),c(d[o+4]),c(d[o+5]),c(d[o+6]),c(d[o+7]),c(d[o+8]),c(d[o+9]),c(d[o+10]),c(d[o+11]),c(d[o+12]),c(d[o+13]),c(d[o+14]),c(d[o+15])
#define RW(x) "+f"(x)
#define WO(x) "=f"(x)
#define R64(d) X16(RW, d, 0), X16(RW, d, 16), X16(RW, d, 32), X16(RW, d, 48)
#define W64(d) X16(WO, d, 0), X16(WO, d, 16), X16(WO, d, 32), X16(WO, d, 48)
#define R16(d) X16(RW, d, 0)
#define WO16(d) X16(WO, d, 0)
#define L64 "{%0,%1,%2,%3,%4,%5,%6,%7,%8,%9,%10,%11,%12,%13,%14,%15,%16,%17,%18,%19,%20,%21,%22,%23,%24,%25,%26,%27,%28,%29,%30,%31," \
        "%32,%33,%34,%35,%36,%37,%38,%39,%40,%41,%42,%43,%44,%45,%46,%47,%48,%49,%50,%51,%52,%53,%54,%55,%56,%57,%58,%59,%60,%61,%62,%63}"
#define L16 "{%0,%1,%2,%3,%4,%5,%6,%7,%8,%9,%10,%11,%12,%13,%14,%15}"

template <int TA, int TB> __device__ __forceinline__ void ss128(float* d, uint64_t a, uint64_t b) {
    asm volatile("wgmma.mma_async.sync.aligned.m64n128k16.f32.bf16.bf16 " L64 ", %64, %65, 1, 1, 1, %66, %67;\n" : R64(d) : "l"(a), "l"(b), "n"(TA), "n"(TB));
}
template <int TA, int TB> __device__ __forceinline__ void ss128_p(float* d, uint64_t a, uint64_t b, int acc) {
    asm volatile("{\n.reg .pred p;\nsetp.ne.s32 p, %68, 0;\nwgmma.mma_async.sync.aligned.m64n128k16.f32.bf16.bf16 " L64 ", %64, %65, p, 1, 1, %66, %67;\n}\n" : R64(d) : "l"(a), "l"(b), "n"(TA), "n"(TB), "r"(acc));
}
template <int TA, int TB> __device__ __forceinline__ void ss128_z(float* d, uint64_t a, uint64_t b) {
    asm volatile("wgmma.mma_async.sync.aligned.m64n128k16.f32.bf16.bf16 " L64 ", %64, %65, 0, 1, 1, %66, %67;\n" : W64(d) : "l"(a), "l"(b), "n"(TA), "n"(TB));
}
__device__ __forceinline__ void rs32(float* d, uint32_t a0, uint32_t a1, uint32_t a2, uint32_t a3, uint64_t b) {
    asm volatile("wgmma.mma_async.sync.aligned.m64n32k16.f32.bf16.bf16 " L16 ", {%16,%17,%18,%19}, %20, 1, 1, 1, 0;\n"
        : R16(d) : "r"(a0), "r"(a1), "r"(a2), "r"(a3), "l"(b));
}
__device__ __forceinline__ void rs32_z(float* d, uint32_t a0, uint32_t a1, uint32_t a2, uint32_t a3, uint64_t b) {
    asm volatile("wgmma.mma_async.sync.aligned.m64n32k16.f32.bf16.bf16 " L16 ", {%16,%17,%18,%19}, %20, 0, 1, 1, 0;\n"
        : WO16(d) : "r"(a0), "r"(a1), "r"(a2), "r"(a3), "l"(b));
}
__device__ __forceinline__ void stsm_x4(uint32_t addr, uint32_t r0, uint32_t r1, uint32_t r2, uint32_t r3) {
    asm volatile("stmatrix.sync.aligned.m8n8.x4.shared.b16 [%0], {%1, %2, %3, %4};" :: "r"(addr), "r"(r0), "r"(r1), "r"(r2), "r"(r3) : "memory");
}
__device__ __forceinline__ uint32_t lds32(uint32_t a) { uint32_t v; asm volatile("ld.shared.u32 %0, [%1];" : "=r"(v) : "r"(a) : "memory"); return v; }
__device__ __forceinline__ uint2 lds64(uint32_t a) { uint2 v; asm volatile("ld.shared.v2.u32 {%0, %1}, [%2];" : "=r"(v.x), "=r"(v.y) : "r"(a) : "memory"); return v; }
__device__ __forceinline__ uint4 lds128(uint32_t a) { uint4 v; asm volatile("ld.shared.v4.u32 {%0, %1, %2, %3}, [%4];" : "=r"(v.x), "=r"(v.y), "=r"(v.z), "=r"(v.w) : "r"(a) : "memory"); return v; }
__device__ __forceinline__ void sts32(uint32_t a, uint32_t x) { asm volatile("st.shared.u32 [%0], %1;" :: "r"(a), "r"(x) : "memory"); }
__device__ __forceinline__ void sts128(uint32_t a, uint32_t x, uint32_t y, uint32_t z, uint32_t w) {
    asm volatile("st.shared.v4.u32 [%0], {%1, %2, %3, %4};" :: "r"(a), "r"(x), "r"(y), "r"(z), "r"(w) : "memory");
}
__device__ __forceinline__ float bflo(uint32_t v) { return __uint_as_float(v << 16); }
__device__ __forceinline__ float bfhi(uint32_t v) { return __uint_as_float(v & 0xffff0000u); }
__device__ __forceinline__ uint32_t hmul2bf(uint32_t a, uint32_t b) { uint32_t r; asm("mul.rn.bf16x2 %0, %1, %2;" : "=r"(r) : "r"(a), "r"(b)); return r; }
__device__ __forceinline__ void mbar_init(uint32_t a, uint32_t c) { asm volatile("mbarrier.init.shared.b64 [%0], %1;" :: "r"(a), "r"(c)); }
__device__ __forceinline__ void mbar_wait(uint32_t a, uint32_t ph) {
    asm volatile("{\n.reg .pred p;\n.reg .u32 n;\nmov.u32 n, 0;\nWAIT_LOOP:\nmbarrier.try_wait.parity.shared.b64 p, [%0], %1;\n@p bra DONE;\nadd.u32 n, n, 1;\nsetp.lt.u32 p, n, 4000000;\n@p bra WAIT_LOOP;\nDONE:\n}" :: "r"(a), "r"(ph) : "memory");
}
__device__ __forceinline__ void mbar_wait_n(uint32_t a, uint32_t ph, uint32_t& n) {
    asm volatile("{\n.reg .pred p;\nWAIT_LOOP:\nmbarrier.try_wait.parity.shared.b64 p, [%1], %2;\n@p bra DONE;\nadd.u32 %0, %0, 1;\nsetp.lt.u32 p, %0, 4000000;\n@p bra WAIT_LOOP;\nDONE:\n}" : "+r"(n) : "r"(a), "r"(ph) : "memory");
}
__device__ __forceinline__ void mbar_expect_tx(uint32_t a, uint32_t bytes) { asm volatile("mbarrier.arrive.expect_tx.shared.b64 _, [%0], %1;" :: "r"(a), "r"(bytes) : "memory"); }
__device__ __forceinline__ void mbar_arrive(uint32_t a) { asm volatile("mbarrier.arrive.shared.b64 _, [%0];" :: "r"(a) : "memory"); }
__device__ __forceinline__ void mbar_arrive2(uint32_t a) { asm volatile("mbarrier.arrive.shared.b64 _, [%0], 2;" :: "r"(a) : "memory"); }
__device__ __forceinline__ void tma_load_2d(uint32_t dst, const CUtensorMap* map, int c0, int c1, uint32_t bar) {
    asm volatile("cp.async.bulk.tensor.2d.shared::cluster.global.mbarrier::complete_tx::bytes [%0], [%1, {%3, %4}], [%2];"
        :: "r"(dst), "l"(map), "r"(bar), "r"(c0), "r"(c1) : "memory");
}
__device__ __forceinline__ void tma_load_3d(uint32_t dst, const CUtensorMap* map, int c0, int c1, int c2, uint32_t bar) {
    asm volatile("cp.async.bulk.tensor.3d.shared::cluster.global.mbarrier::complete_tx::bytes [%0], [%1, {%3, %4, %5}], [%2];"
        :: "r"(dst), "l"(map), "r"(bar), "r"(c0), "r"(c1), "r"(c2) : "memory");
}
__device__ __forceinline__ void tma_load_4d(uint32_t dst, const CUtensorMap* map, int c0, int c3, uint32_t bar) {
    asm volatile("cp.async.bulk.tensor.4d.shared::cluster.global.mbarrier::complete_tx::bytes [%0], [%1, {%3, %5, %5, %4}], [%2];"
        :: "r"(dst), "l"(map), "r"(bar), "r"(c0), "r"(c3), "r"(0) : "memory");
}
__device__ __forceinline__ void tma_load_5d(uint32_t dst, const CUtensorMap* map, int c0, int c4, uint32_t bar) {
    asm volatile("cp.async.bulk.tensor.5d.shared::cluster.global.mbarrier::complete_tx::bytes [%0], [%1, {%3, %5, %5, %5, %4}], [%2];"
        :: "r"(dst), "l"(map), "r"(bar), "r"(c0), "r"(c4), "r"(0) : "memory");
}
__device__ __forceinline__ void bulk_load(uint32_t dst, const void* src, uint32_t bytes, uint32_t bar) {
    asm volatile("cp.async.bulk.shared::cluster.global.mbarrier::complete_tx::bytes [%0], [%1], %2, [%3];" :: "r"(dst), "l"(src), "r"(bytes), "r"(bar) : "memory");
}
__device__ __forceinline__ void wait_counter(const unsigned int* p, unsigned int target) {
    unsigned int cur; int spins = 0;
    #pragma unroll 1
    do {
        asm volatile("ld.relaxed.gpu.global.u32 %0, [%1];" : "=r"(cur) : "l"(p) : "memory");
        if ((int)(cur - target) >= 0) break;
        __nanosleep(20);
    } while (++spins < (1 << 22));
}
__device__ __forceinline__ void red_release(unsigned int* p) { asm volatile("red.release.gpu.global.add.u32 [%0], 1;" :: "l"(p) : "memory"); }
__device__ __forceinline__ uint32_t clk32() { uint32_t c; asm volatile("mov.u32 %0, %%clock;" : "=r"(c)); return c; }
__device__ __forceinline__ bool elect_one() {
    uint32_t r;
    asm volatile("{\n.reg .pred p;\nelect.sync _|p, 0xffffffff;\nselp.u32 %0, 1, 0, p;\n}" : "=r"(r));
    return r != 0;
}
__device__ __forceinline__ int tid128() { int t; asm volatile("mov.u32 %0, %%tid.x;" : "=r"(t)); return t & 127; }
typedef __nv_bfloat162 bf2;
__device__ __forceinline__ bf2 asbf2(uint32_t v) { return *reinterpret_cast<bf2*>(&v); }
__device__ __forceinline__ uint32_t asu32(bf2 v) { return *reinterpret_cast<uint32_t*>(&v); }
template <int M> struct W16 { static constexpr uint32_t c = ct::bf16bits(ct::cos2048(128 * M)) * 0x10001u, s = ct::bf16bits(-ct::sin2048(128 * M)) * 0x10001u; };
__device__ __forceinline__ void pin(bf2& v) { uint32_t u = asu32(v); asm volatile("" : "+r"(u) :: "memory"); v = asbf2(u); }
__device__ __forceinline__ bf2 neg2(bf2 v) { return asbf2(asu32(v) ^ 0x80008000u); }
__device__ __forceinline__ void cmul2(bf2& r, bf2& i, bf2 wr, bf2 wi) {
    const bf2 a = r, b = i;
    r = __hfma2(a, wr, __hmul2(b, neg2(wi))); i = __hfma2(b, wr, __hmul2(a, wi));
}
__device__ __forceinline__ void bfly4(bf2* r, bf2* i, int o, int s) {
    const bf2 ar = __hadd2(r[o], r[o + 2 * s]), ai = __hadd2(i[o], i[o + 2 * s]), br = __hsub2(r[o], r[o + 2 * s]), bi = __hsub2(i[o], i[o + 2 * s]);
    const bf2 cr = __hadd2(r[o + s], r[o + 3 * s]), ci = __hadd2(i[o + s], i[o + 3 * s]), dr = __hsub2(r[o + s], r[o + 3 * s]), di = __hsub2(i[o + s], i[o + 3 * s]);
    r[o] = __hadd2(ar, cr); i[o] = __hadd2(ai, ci); r[o + 2 * s] = __hsub2(ar, cr); i[o + 2 * s] = __hsub2(ai, ci);
    r[o + s] = __hadd2(br, di); i[o + s] = __hsub2(bi, dr); r[o + 3 * s] = __hsub2(br, di); i[o + 3 * s] = __hadd2(bi, dr);
}
template <int M> __device__ __forceinline__ void tw16(bf2& r, bf2& i) {
    if (M == 4) { const bf2 a = r; r = i; i = neg2(a); }
    else cmul2(r, i, asbf2(W16<M>::c), asbf2(W16<M>::s));
}
__device__ __forceinline__ void tw16_all(bf2* r, bf2* i) {
    tw16<1>(r[5], i[5]); tw16<2>(r[6], i[6]); tw16<3>(r[7], i[7]); tw16<2>(r[9], i[9]); tw16<4>(r[10], i[10]); tw16<6>(r[11], i[11]);
    tw16<3>(r[13], i[13]); tw16<6>(r[14], i[14]); tw16<9>(r[15], i[15]);
}

__device__ __forceinline__ void dft16(bf2* r, bf2* i) {
    #pragma unroll
    for (int r0 = 0; r0 < 4; r0++) bfly4(r, i, r0, 4);
    tw16_all(r, i);
    #pragma unroll
    for (int k1 = 0; k1 < 4; k1++) bfly4(r, i, 4 * k1, 1);
}
__device__ __forceinline__ void idft16(bf2* r, bf2* i) {
    #pragma unroll
    for (int k1 = 0; k1 < 4; k1++) bfly4(i, r, 4 * k1, 1);
    tw16_all(i, r);
    #pragma unroll
    for (int r0 = 0; r0 < 4; r0++) bfly4(i, r, r0, 4);
}

#define DBAR 1
#define FBAR 2
#define TBAR 4
#define HBAR 6
#define GBAR 10
#define LBAR 11
#define FULL(s) (bars + 8 * (s))
#define EMPTY(s) (bars + 8 * (RING + (s)))
#define XB (bars + 64)
#define X1B(h) (bars + 72 + 8 * (h))
#define ZOK (bars + 88)
#define EPB (bars + 96)
#define R0F (bars + 104)
#define HOK(i) (bars + 112 + 8 * (i))
#define WQ(i) (bars + 144 + 8 * (i))
#define EPO_OFF (BAR_OFF + 176)
#define ROLE_OFF (BAR_OFF + 180)
#define SACT_OFF (BAR_OFF + 184)
#define PT_OFF (R2 + 26624)
#define LAM_OFF (R2 + 27648)
#define WBUF(i) ((i) == 1 ? R1 : ((i) == 2 ? R1 + 16384 : R2 + 10240))
#define PC1 448
#define PC1M 256
#define P1END 8500
#define PC2 88
#define PCR 96
#define PCH 160
#define PCL 100
#define PCW 200
#define TTAB 8500
#define PFW 5000
#define PFB 9000
#define PFC 12000
#define PFCS 2000
__device__ __forceinline__ void delay(int cycles) { const uint32_t c = clk32(); while ((int)(clk32() - c) < cycles) { } }
__device__ __forceinline__ void pace(uint32_t& t, int cycles) { while ((int)(clk32() - t) < 0) { } t += cycles; }
__device__ __forceinline__ void pf_line(const void* p) { asm volatile("prefetch.global.L2 [%0];" :: "l"(p)); }

__device__ __forceinline__ float2 cis(int m) { return __ldg(reinterpret_cast<const float2*>(g_img.cs[m & 15][(m >> 4) & 127])); }
__device__ __forceinline__ void gen_dft(uint32_t dst, int j, float2 w, float2 b, int b0, int b1, float c0) {
    const float c2 = 2.f * w.x;
    float2 a = cmul(b, w);
    float2 z0 = b0 ? b : make_float2(c0, (j & 1) ? -c0 : c0);
    dst += j * 128;
    #pragma unroll 1
    for (int blk = b0; blk < b1; blk++) {
        float2 v[9];
        v[0] = b;
        v[1] = make_float2(fmaf(c2, b.x, -a.x), fmaf(c2, b.y, -a.y));
        #pragma unroll
        for (int k = 2; k < 9; k++) v[k] = make_float2(fmaf(c2, v[k - 1].x, -v[k - 2].x), fmaf(c2, v[k - 1].y, -v[k - 2].y));
        const uint32_t p = dst + (blk >> 2) * 16384, c = (2 * (blk & 3)) ^ (j & 7);
        sts128(p + c * 16, pack2(z0.x, v[1].x), pack2(v[2].x, v[3].x), pack2(v[4].x, v[5].x), pack2(v[6].x, v[7].x));
        sts128(p + (c ^ 1) * 16, pack2(z0.y, v[1].y), pack2(v[2].y, v[3].y), pack2(v[4].y, v[5].y), pack2(v[6].y, v[7].y));
        a = v[7]; b = v[8]; z0 = b;
    }
}

__device__ __forceinline__ void fft_p1(uint32_t sbase, uint32_t bars, int tile, int r, int db, uint32_t t_end) {
    constexpr uint32_t s16 = SBASE / 16;
    float acc[64];
    wgmma_fence();
    ss128_z<1, 1>(acc, mkd(s16 + tile * 1024, R1, 16384, 1024, 1), mkd(s16, R0, 16384, 1024, 1));
    #pragma unroll
    for (int ks = 1; ks < 8; ks++) ss128<1, 1>(acc, mkd(s16 + tile * 1024, R1 + ks * 2048, 16384, 1024, 1), mkd(s16, R0 + ks * 2048, 16384, 1024, 1));
    wgmma_commit();
    const int tid = tid128();
    float g0 = 0.f;
    uint4* dst = g_X1 + (64 * tile + 2 * (tid >> 2)) * 2048 + (r >> 3) * 1024 + db * 128 + (r & 7) * 16 + (tid & 3);
    wgmma_wait<0>();
    reg_fence<64>(acc);
    uint32_t tp = clk32();
    const int dt = min(max((int)(t_end - tp) >> 3, PC1M), PC1);
    tp += (threadIdx.x >> 5 & 7) * (dt >> 3);
    #pragma unroll
    for (int c = 0; c < 4; c++) {
        const float* u = acc + 4 * (c >> 1) + (c & 1);
        #pragma unroll
        for (int ke = 0; ke < 2; ke++) {
            float v[8];
            #pragma unroll
            for (int z = 0; z < 8; z++) { const int ix = 8 * (z & 3) + 2 * (z >> 2); v[z] = ke ? u[ix] - u[ix + 32] : u[ix] + u[ix + 32]; }
            uint4 o = make_uint4(pack2(v[0], v[1]), pack2(v[2], v[3]), pack2(v[4], v[5]), pack2(v[6], v[7]));
            asm volatile("" : "+r"(o.x), "+r"(o.y), "+r"(o.z), "+r"(o.w) :: "memory");
            pace(tp, dt);
            __stcg(dst + ke * 2048 + 4 * c, o);
            if (c < 2) {
                #pragma unroll
                for (int k = 4 * c + 2 * ke; k < 4 * c + 2 * ke + 2; k++) {
                    const uint4 x = lds128(sbase + R0 + tile * 16384 + tid * 128 + ((k ^ (tid & 7)) << 4)), gv = lds128(sbase + GATE_OFF + tile * 128 + k * 16);
                    const uint32_t p0 = hmul2bf(x.x, gv.x), p1 = hmul2bf(x.y, gv.y), p2 = hmul2bf(x.z, gv.z), p3 = hmul2bf(x.w, gv.w);
                    g0 += ((bflo(p0) + bfhi(p0)) + (bflo(p1) + bfhi(p1))) + ((bflo(p2) + bfhi(p2)) + (bflo(p3) + bfhi(p3)));
                }
            }
            if (c == 1 && ke == 1) {
                __stcg(&g_gp[(16 * r + 2 * db + tile) * 128 + tid], g0);
                __syncwarp();
                if ((tid & 31) == 0) mbar_arrive(R0F);
            }
        }
    }
}

__device__ __forceinline__ int w_first(int unit, int hb) { const int ka = unit >> 1, ke = unit & 1; return hb ? ((128 - ka) & 127) * 513 + 2 - ke : ka * 513 + ke; }
__device__ __forceinline__ void load_w(const CUtensorMap* wm, uint32_t sbase, int unit, int i) {
    const uint32_t bars = sbase + BAR_OFF;
    mbar_expect_tx(WQ(i), 16384);
    #pragma unroll 1
    for (int a = 0; a < 4; a++) { tma_load_3d(sbase + WBUF(i) + a * 4096, wm + (i & 1), w_first(unit, i >> 1) & ~15, 0, 4 * a, WQ(i)); delay(PCW); }
}
__device__ __forceinline__ uint32_t w_off(int e) { e &= 511; return (e >> 6) * 128 + ((((e >> 3) ^ (e >> 6)) & 7) << 4) + (e & 7) * 2; }
__device__ __forceinline__ void sts16(uint32_t a, uint32_t v) { asm volatile("st.shared.u16 [%0], %1;" :: "r"(a), "h"((unsigned short)v) : "memory"); }
__device__ __forceinline__ void boundary() { while (clk32() == 0) { } asm volatile("" ::: "memory"); }
__device__ __forceinline__ void yield_to_scan(uint32_t sbase) {
    #pragma unroll 1
    for (int n = 0; n < 100000 && lds32(sbase + SACT_OFF); n++) __nanosleep(50);
}
template <int OFF> __device__ __forceinline__ uint32_t lds_w(uint32_t a, uint32_t b) {
    uint32_t l, h;
    asm volatile("ld.shared.u16 %0, [%2 + %4];\nld.shared.u16 %1, [%3 + %4];" : "=r"(l), "=r"(h) : "r"(a), "r"(b), "n"(OFF) : "memory");
    return __byte_perm(l, h, 0x5410);
}
template <int S> __device__ __forceinline__ void load_ws(uint32_t* w, uint32_t a, uint32_t b) {
    if constexpr (S < 16) { w[S] = lds_w<((S >> 2) + 4 * (S & 3)) * 1024>(a, b); load_ws<S + 1>(w, a, b); }
}
template <int I> __device__ __forceinline__ void fetch_w(uint32_t* w, uint32_t sbase, int unit) {
    constexpr int hb = I >> 1;
    const uint32_t bars = sbase + BAR_OFF, buf = sbase + WBUF(I);
    const int tid = tid128(), sh = w_first(unit, hb) & 15;
    const uint32_t pt = lds32(sbase + PT_OFF + 512 * hb + 4 * tid) >> (16 * (I & 1)), sp = lds32(sbase + DSK_OFF + 4 * (tid & 31)) >> (16 * (I & 1));
    mbar_wait(WQ(I), 0);
    if ((sh & 1) + 2 * (tid & 7) + 2 <= sh) sts16(buf + (tid >> 3) * 1024 + ((sh & 1) + 2 * (tid & 7)) * 2, pt);
    bar_sync_n(FBAR, 128);
    if (!(unit & 1) && (tid >> 4) == hb) sts16(buf + w_off(sh + 510 * hb) + (tid & 15) * 1024, sp);
    __syncwarp();
    boundary();
    const int pos = 128 * (tid & 3) + 2 * (tid >> 2);
    const bool rot = hb && unit >= 2;
    const uint32_t o0 = buf + w_off(sh + (hb ? 510 - pos : pos)) - (rot ? 1024 : 0), o1 = buf + w_off(sh + (hb ? 446 - pos : pos + 64)) - (rot ? 1024 : 0), oz = rot ? 16384 : 0;
    w[0] = lds_w<0>(o0 + oz, o1 + oz);
    load_ws<1>(w, o0, o1);
}
__device__ __forceinline__ void pin16(bf2* r, bf2* i) {
    #pragma unroll
    for (int k = 0; k < 16; k++) { pin(r[k]); pin(i[k]); }
}

__device__ __forceinline__ void fft_p2(uint32_t sbase, uint32_t bars, int unit, const __nv_bfloat16* w_r, const __nv_bfloat16* w_i) {
    constexpr uint32_t s16 = SBASE / 16;
    const ct::Half* tb = &g_img.h[unit & 1];
    uint32_t P[16][4];
    uint32_t wr[16], wi[16];
    {
        const int tid = tid128();
        uint32_t sp = 0, pt[2] = {0, 0};
        const uint4 t = __ldg(reinterpret_cast<const uint4*>(tb->tw[0][tid]));
        if (tid < 32 && !(unit & 1)) {
            const int k1 = ((tid & 16) ? (128 - (unit >> 1)) & 127 : unit >> 1) + 128 * (tid & 15), o1 = k1 * 513 + 32 * (tid & 16), o2 = ((2048 - k1) & 2047) * 513 + 32 * (tid & 16);
            sp = pack2(0.5f * (__bfloat162float(w_r[o1]) + __bfloat162float(w_r[o2])), 0.5f * (__bfloat162float(w_i[o1]) - __bfloat162float(w_i[o2])));
        }
        #pragma unroll
        for (int hb = 0; hb < 2; hb++) {
            const int e0 = w_first(unit, hb), z = (e0 & 1) + 2 * (tid & 7), o = (tid >> 3) * 65664 + (e0 & ~15) + 512 + z;
            if (z + 2 <= (e0 & 15)) pt[hb] = reinterpret_cast<const unsigned short*>(w_r)[o] | ((uint32_t)reinterpret_cast<const unsigned short*>(w_i)[o] << 16);
        }
        sts32(sbase + PT_OFF + 4 * tid, pt[0]); sts32(sbase + PT_OFF + 512 + 4 * tid, pt[1]);
        mbar_wait(X1B(0), 0);
        if (tid < 32) sts32(sbase + DSK_OFF + 4 * tid, sp);
        if (unit >= 128) {
            mbar_wait(X1B(1), 0);
            #pragma unroll 1
            for (int i = 0; i < 16; i++) {
                const float2 w = cis(-64 * ((i & 8) + (tid >> 4)));
                const uint32_t a = sbase + R1 + (i * 128 + tid) * 16;
                const uint2 v = lds64(a + 8);
                sts128(a, pack2(bflo(v.x) * w.x, bfhi(v.x) * w.x), pack2(bflo(v.y) * w.x, bfhi(v.y) * w.x), pack2(bflo(v.x) * w.y, bfhi(v.x) * w.y), pack2(bflo(v.y) * w.y, bfhi(v.y) * w.y));
            }
            fence_async();
            bar_sync_n(FBAR, 128);
        }
        #pragma unroll
        for (int h = 0; h < 2; h++) {
            float acc[64];
            if (h) mbar_wait(X1B(1), 0);
            wgmma_fence();
            ss128_z<1, 0>(acc, mkd(s16, R2, 1024, 128), mkd(s16, R1 + h * 16384, 2048, 128));
            #pragma unroll
            for (int s = 1; s < 4; s++) ss128<1, 0>(acc, mkd(s16, R2 + s * 2048, 1024, 128), mkd(s16, R1 + h * 16384 + s * 4096, 2048, 128));
            wgmma_commit();
            if (h == 1) {
                fetch_w<0>(wr, sbase, unit);
                #pragma unroll
                for (int s = 0; s < 16; s++) asm volatile("" : "+r"(wr[s]) :: "memory");
                if (unit > 999) sts32(sbase + SACT_OFF + 4, wr[15]);
            }
            wgmma_wait<0>();
            reg_fence<64>(acc);
            bar_arrive_n(LBAR + h, 160);
            bf2 f[32];
            #pragma unroll
            for (int z = 0; z < 32; z++) { uint32_t u = pack2(acc[2 * z], acc[2 * z + 1]); asm volatile("" : "+r"(u) :: "memory"); f[z] = asbf2(u); }
            boundary();
            float d[2][16];
            #pragma unroll
            for (int pr = 0; pr < 5; pr++) {
                if (pr == 2) boundary();
                if (pr < 4) {
                    bf2* a = f + 8 * pr;
                    #pragma unroll
                    for (int z = 0; z < 8; z++) pin(a[z]);
                    #pragma unroll
                    for (int z = 0; z < 4; z++) cmul2(a[2 * z], a[2 * z + 1], asbf2((z & 1) ? t.z : t.x), asbf2((z & 1) ? t.w : t.y));
                    wgmma_fence();
                    rs32_z(d[pr & 1], asu32(a[0]), asu32(a[4]), asu32(a[2]), asu32(a[6]), mkd(s16, B16F_OFF, 128, 512));
                    rs32(d[pr & 1], asu32(a[1]), asu32(a[5]), asu32(a[3]), asu32(a[7]), mkd(s16, B16F_OFF + 256, 128, 512));
                    wgmma_commit();
                }
                if (pr > 0) {
                    if (pr < 4) wgmma_wait<1>(); else wgmma_wait<0>();
                    reg_fence<16>(d[(pr - 1) & 1]);
                    #pragma unroll
                    for (int z = 0; z < 8; z++) {
                        uint32_t& p = P[8 * h + 2 * pr - 2 + (z & 1)][z >> 1];
                        p = pack2(d[(pr - 1) & 1][2 * z], d[(pr - 1) & 1][2 * z + 1]);
                        asm volatile("" : "+r"(p) :: "memory");
                    }
                }
            }
        }
    }
    {
        bf2 vr[2][16], vi[2][16];
        #pragma unroll
        for (int r = 0; r < 16; r++) { vr[0][r] = asbf2(P[r][0]); vr[1][r] = asbf2(P[r][1]); vi[0][r] = asbf2(P[r][2]); vi[1][r] = asbf2(P[r][3]); }
        fetch_w<1>(wi, sbase, unit);
        pin16(vr[0], vi[0]);
        dft16(vr[0], vi[0]);
        #pragma unroll
        for (int s = 0; s < 16; s++) cmul2(vr[0][s], vi[0][s], asbf2(wr[s]), asbf2(wi[s]));
        fetch_w<2>(wr, sbase, unit);
        pin16(vr[1], vi[1]);
        dft16(vr[1], vi[1]);
        fetch_w<3>(wi, sbase, unit);
        pin16(vr[0], vi[0]);
        idft16(vr[0], vi[0]);
        #pragma unroll
        for (int s = 0; s < 16; s++) cmul2(vr[1][s], vi[1][s], asbf2(wr[s]), asbf2(wi[s]));
        bar_sync_n(FBAR, 128);
        idft16(vr[1], vi[1]);
        #pragma unroll
        for (int r = 0; r < 16; r++) { P[r][0] = asu32(vr[0][r]); P[r][1] = asu32(vr[1][r]); P[r][2] = asu32(vi[0][r]); P[r][3] = asu32(vi[1][r]); }
    }
    {
        const int tid = tid128(), ka = unit >> 1;
        const uint4 t = __ldg(reinterpret_cast<const uint4*>(tb->tw[1][tid]));
        const uint32_t zero = unit >> 8;
        const uint32_t sa = sbase + R1 + ((tid >> 3) & 1) * 1024 + (2 * (tid >> 5) + ((tid >> 4) & 1)) * 128 + (tid & 7) * 16;
        uint8_t* dst = reinterpret_cast<uint8_t*>(g_X2) + (2 * (tid >> 5)) * X2_IMG + (unit & 1) * (X2_IMG / 2)
                     + (16 * (ka >> 3) + 8 * ((tid >> 4) & 1) + (ka & 7)) * 128 + ((((tid >> 1) & 7) ^ (ka & 7)) << 4) + (tid & 1) * 8;
        uint32_t o[32];
        #pragma unroll
        for (int h = 0; h < 2; h++) {
            float d[2][16];
            #pragma unroll
            for (int pr = 0; pr < 5; pr++) {
                if (!(pr & 1)) { if (h) yield_to_scan(sbase); else boundary(); }
                if (pr < 4) {
                    uint32_t a[8];
                    #pragma unroll
                    for (int z = 0; z < 8; z++) asm volatile("xor.b32 %0, %1, %2;" : "=r"(a[z]) : "r"(P[8 * h + 2 * pr + (z >> 2)][z & 3]), "r"(zero) : "memory");
                    wgmma_fence();
                    rs32_z(d[pr & 1], a[0], a[4], a[1], a[5], mkd(s16, R2 + 8192, 128, 512));
                    rs32(d[pr & 1], a[2], a[6], a[3], a[7], mkd(s16, R2 + 8192 + 256, 128, 512));
                    wgmma_commit();
                }
                if (h) {
                    #pragma unroll
                    for (int z = 2 * pr; z < 2 * pr + 2; z++) __stcg(reinterpret_cast<uint2*>(dst + (8 * (z >> 1) + (z & 1)) * X2_IMG), make_uint2(o[2 * z], o[2 * z + 1]));
                }
                if (pr > 0) {
                    if (pr < 4) wgmma_wait<1>(); else wgmma_wait<0>();
                    reg_fence<16>(d[(pr - 1) & 1]);
                    #pragma unroll
                    for (int rl = 0; rl < 2; rl++) {
                        const float* a = d[(pr - 1) & 1] + 2 * rl;
                        bf2 r0 = asbf2(pack2(a[0], a[1])), r1 = asbf2(pack2(a[4], a[5])), i0 = asbf2(pack2(a[8], a[9])), i1 = asbf2(pack2(a[12], a[13]));
                        cmul2(r0, i0, asbf2(t.x), asbf2(t.y)); cmul2(r1, i1, asbf2(t.z), asbf2(t.w));
                        stsm_x4(sa + (8 * h + 2 * pr - 2 + rl) * 2048, asu32(r0), asu32(r1), asu32(i0), asu32(i1));
                    }
                }
            }
            fence_async();
            bar_sync_n(FBAR, 128);
            boundary();
            float acc[64];
            wgmma_fence();
            ss128_z<0, 1>(acc, mkd(s16, R2, 128, 1024), mkd(s16, R1 + h * 16384, 128, 1024));
            #pragma unroll
            for (int s = 1; s < 4; s++) ss128<0, 1>(acc, mkd(s16, R2 + s * 256, 128, 1024), mkd(s16, R1 + h * 16384 + s * 256, 128, 1024));
            wgmma_commit();
            uint32_t tp = clk32();
            if (h) {
                #pragma unroll
                for (int z = 10; z < 16; z++) { if (!(z & 1)) pace(tp, 2 * PC2); __stcg(reinterpret_cast<uint2*>(dst + (8 * (z >> 1) + (z & 1)) * X2_IMG), make_uint2(o[2 * z], o[2 * z + 1])); }
            }
            wgmma_wait<0>();
            reg_fence<64>(acc);
            #pragma unroll
            for (int z = 0; z < 16; z++) { const float* a = acc + 8 * (z >> 1) + 2 * (z & 1); o[2 * z] = pack2(a[0], a[1]); o[2 * z + 1] = pack2(a[4], a[5]); asm volatile("" : "+r"(o[2 * z]), "+r"(o[2 * z + 1]) :: "memory"); }
            if (h) {
                yield_to_scan(sbase);
                tp = clk32() + (tid >> 5) * (PC2 / 2);
                #pragma unroll
                for (int z = 0; z < 16; z++) { if (!(z & 1)) pace(tp, 2 * PC2); __stcg(reinterpret_cast<uint2*>(dst + (64 + 8 * (z >> 1) + (z & 1)) * X2_IMG), make_uint2(o[2 * z], o[2 * z + 1])); }
            }
        }
    }
}

struct Maps { CUtensorMap BB, X, Xr, Cre, Cim, W[2]; };

template <int S> __device__ __forceinline__ void release(uint32_t rel, uint32_t bars) {
    mbar_arrive(EMPTY(S));
    asm volatile("mbarrier.arrive.shared::cluster.b64 _, [%0 + %1];" :: "r"(rel), "n"(8 * (RING + S)) : "memory");
}
__device__ __forceinline__ int peer_role(uint32_t a) { int v; asm volatile("ld.shared::cluster.u32 %0, [%1];" : "=r"(v) : "r"(a ^ (1u << 24)) : "memory"); return v; }
__device__ __forceinline__ void tma_load_3d_mc(uint32_t dst, const CUtensorMap* map, int c0, int c1, int c2, uint32_t bar) {
    asm volatile("cp.async.bulk.tensor.3d.shared::cluster.global.mbarrier::complete_tx::bytes.multicast::cluster [%0], [%1, {%3, %4, %5}], [%2], %6;"
        :: "r"(dst), "l"(map), "r"(bar), "r"(c0), "r"(c1), "r"(c2), "h"((unsigned short)3) : "memory");
}
__device__ __forceinline__ void bulk_load_mc(uint32_t dst, const void* src, uint32_t bytes, uint32_t bar) {
    asm volatile("cp.async.bulk.shared::cluster.global.mbarrier::complete_tx::bytes.multicast::cluster [%0], [%1], %2, [%3], %4;"
        :: "r"(dst), "l"(src), "r"(bytes), "r"(bar), "h"((unsigned short)3) : "memory");
}
template <int TA> __device__ __forceinline__ void mma_round(float* acc, uint32_t bars, uint32_t a16, uint32_t ph, bool lead, int accum, int it, uint32_t& nw, uint32_t peer, int pp, bool lag = false) {
    #pragma unroll
    for (int s = 0; s < RING; s++) {
        if (TA && (s == 1 || s == 2) && lag) bar_sync_n(TBAR + s - 1, 256);
        mbar_wait_n(FULL(s), ph, nw);
        if (!TA || accum < 7 || (s == 0 && !lag)) bar_sync_n(pp, 256);
        wgmma_fence();
        #pragma unroll
        for (int k = 0; k < 4; k++) {
            const uint64_t da = TA ? mkd(a16, s * STGB + k * 256, 128, 1024) : mkd(a16, s * STGB + k * 32, 16, 1024, 1);
            const uint64_t db = mkd(SBASE / 16, s * STGB + 16384 + k * 32, 16, 1024, 1);
            if (k == 0 && s == 0) ss128_p<TA, 0>(acc, da, db, accum); else ss128<TA, 0>(acc, da, db);
        }
        wgmma_commit();
        if (!TA || accum < 7) bar_arrive_n(14 - pp, 256);
        wgmma_wait<1>();
        if (lead && (s > 0 ? (!TA || accum < 7) : accum != 0)) { if (s == 0) release<3>(peer, bars); if (s == 1) release<0>(peer, bars); if (s == 2) release<1>(peer, bars); if (s == 3) release<2>(peer, bars); }
    }
}
__device__ __forceinline__ void gemm_main(float* A, uint32_t sbase, int wg, int warp, int lane, int cb, int tc, int swp) {
    const uint32_t bars = sbase + BAR_OFF;
    const bool lead = tid128() == 0;
    const uint32_t a16 = SBASE / 16 + wg * 512;
    uint32_t nw = 0;
    uint32_t peer = bars ^ ((uint32_t)(lane + 1) << 24);
    asm volatile("" : "+r"(peer));
    asm volatile("barrier.cluster.wait.acquire.aligned;" ::: "memory");
    if (wg) bar_arrive_n(0, 256);
    uint32_t a = sbase + R0 + (((lane >> 3) & 1) ^ swp) * 16384 + (lane >> 4) * 1024 + (wg * 32 + warp * 8 + (lane & 7)) * 16;
    uint32_t pa = sbase + LAM_OFF + (wg * 32 + warp * 8 + (lane >> 2)) * 16;
    unsigned long long* ag = &g_agg[tc * P_DIM + cb * 128 + wg * 32 + warp * 8 + (lane >> 2)];
    asm volatile("" : "+r"(a), "+r"(pa), "+l"(ag));
    #pragma unroll 1
    for (int half = 0; half < 2; half++) {
        uint2 p0;
        uint4 p1;
        uint32_t par;
        #pragma unroll 1
        for (int rd = 0; rd < 4; rd++) {
            if (rd == 3) { mbar_wait_n(EPB, 0, nw); p0 = lds64(pa); p1 = lds128(pa + 2048); par = lds32(sbase + EPO_OFF); }
            mma_round<0>(A, bars, a16, rd & 1, lead, rd, 16 * half + 4 * rd, nw, peer, 14 * wg);
        }
        mbar_wait_n(R0F, half, nw);
        const float2 lam = make_float2(__uint_as_float(p0.x), __uint_as_float(p0.y));
        const float2 l16 = make_float2(__uint_as_float(p1.x), __uint_as_float(p1.y)), l32 = make_float2(__uint_as_float(p1.z), __uint_as_float(p1.w)), l64 = cmul(l32, l32);
        wgmma_wait<0>();
        reg_fence<64>(A);
        if (lead) release<RING - 1>(peer, bars);
        #pragma unroll
        for (int r = 1; r < 16; r++) {
            #pragma unroll
            for (int c = 0; c < 2; c++) {
                const float2 v = cfma(lam, make_float2(A[4 * r - 4 + c], A[4 * r - 2 + c]), make_float2(A[4 * r + c], A[4 * r + 2 + c]));
                A[4 * r + c] = v.x; A[4 * r + 2 + c] = v.y;
            }
            if ((r & 1) && r < 12) { const float* u = A + 4 * r - 4; stsm_x4(a + (r >> 1) * 2048, pack2(u[0], u[1]), pack2(u[2], u[3]), pack2(u[4], u[5]), pack2(u[6], u[7])); }
        }
        {
            float2 e = cfma(l16, make_float2(A[60], A[62]), make_float2(A[61], A[63]));
            float2 o = make_float2(__shfl_xor_sync(0xffffffffu, e.x, 1), __shfl_xor_sync(0xffffffffu, e.y, 1));
            stsm_x4(a + 6 * 2048, pack2(A[48], A[49]), pack2(A[50], A[51]), pack2(A[52], A[53]), pack2(A[54], A[55]));
            e = cfma(l32, o, e);
            o = make_float2(__shfl_xor_sync(0xffffffffu, e.x, 2), __shfl_xor_sync(0xffffffffu, e.y, 2));
            stsm_x4(a + 7 * 2048, pack2(A[56], A[57]), pack2(A[58], A[59]), pack2(A[60], A[61]), pack2(A[62], A[63]));
            e = cfma(l64, o, e);
            if ((lane & 3) == 3)
                asm volatile("st.relaxed.gpu.global.v2.u32 [%0], {%1, %2};" :: "l"(ag),
                             "r"((__float_as_uint(swp ? e.y : e.x) & ~1u) | (par & 1u)), "r"((__float_as_uint(swp ? e.x : e.y) & ~1u) | (par & 1u)) : "memory");
        }
        pa += 1024; ag += 64;
        bar_arrive_n(DBAR, 384);
    }
    #pragma unroll 1
    for (int rd = 0; rd < 8; rd++) mma_round<1>(A, bars, a16, rd & 1, lead, rd, 32 + 4 * rd, nw, peer, 14 * wg, rd * wg == 7);
}

__device__ __forceinline__ const CUtensorMap* keep(const CUtensorMap* p) { return reinterpret_cast<const CUtensorMap*>(__shfl_sync(0xffffffffu, reinterpret_cast<unsigned long long>(p), 0)); }
__device__ __forceinline__ void produce(const Maps& mp, uint32_t sbase, int RK, int cb, int tc, int db, int rc) {
    const uint32_t bars = sbase + BAR_OFF;
    const CUtensorMap *mb = keep(&mp.BB), *mx = keep(&mp.X), *cr = keep(&mp.Cre), *ci = keep(&mp.Cim);
    if (!elect_one()) return;
    uint32_t nw = 0;
    int kc = 256, row = cb * 16;
    const int xj = tc * 8, xr = RK * 8;
    #pragma unroll 1
    for (int rd = 1; rd < 8; rd++) {
        #pragma unroll
        for (int s = 0; s < RING; s++) {
            mbar_wait_n(EMPTY(s), (rd - 1) & 1, nw);
            mbar_expect_tx(FULL(s), STGB);
            tma_load_3d_mc(sbase + s * STGB + 16384 + RK * 8192, mx, kc, xj, xr, FULL(s));
            tma_load_4d(sbase + s * STGB, mb, kc, row, FULL(s));
            asm volatile("add.s32 %0, %0, 64;" : "+r"(kc));
        }
        if (rd == 3) { kc = 0; row += 8; }
    }
    const uint8_t* hs = reinterpret_cast<const uint8_t*>(g_h) + rc * 32 * 16384 + RK * 8192;
    const int d0 = db * 4, d1 = db * 4 + 32;
    #pragma unroll 1
    for (int rd = 8; rd < 16; rd++) {
        const CUtensorMap* cm = (rd & 2) ? ci : cr;
        kc = (rd & 1) * 512 + (rd & 4) * 16;
        #pragma unroll
        for (int s = 0; s < RING; s++) {
            mbar_wait_n(EMPTY(s), (rd - 1) & 1, nw);
            mbar_expect_tx(FULL(s), STGB);
            if (s) bulk_load_mc(sbase + s * STGB + RK * 8192, hs, 8192, FULL(s));
            tma_load_5d(sbase + s * STGB + 16384, cm, kc, d0, FULL(s));
            tma_load_5d(sbase + s * STGB + 24576, cm, kc, d1, FULL(s));
            if (s == 0) { mbar_wait_n(HOK((rd >> 1) & 3), 0, nw); }
            if (!s) bulk_load_mc(sbase + s * STGB + RK * 8192, hs, 8192, FULL(s));
            asm volatile("add.s32 %0, %0, 128;" : "+r"(kc));
            asm volatile("add.s64 %0, %0, 16384;" : "+l"(hs));
        }
    }
}

template <bool full> __global__ void __cluster_dims__(2, 1, 1) __launch_bounds__(640, 1)
fused_kernel(const __nv_bfloat16* __restrict__ x, const __nv_bfloat16* __restrict__ Bre, const __nv_bfloat16* __restrict__ Bim, int swp,
             const __nv_bfloat16* __restrict__ w_r, const __nv_bfloat16* __restrict__ w_i,
             const __nv_bfloat16* __restrict__ lam_re, const __nv_bfloat16* __restrict__ lam_im,
             const __nv_bfloat16* __restrict__ log_dt, const __nv_bfloat16* __restrict__ dskip,
             const __nv_bfloat16* __restrict__ gate_w,
             const __nv_bfloat16* __restrict__ Cre, const __nv_bfloat16* __restrict__ Cim, float* __restrict__ out,
             const __grid_constant__ Maps mp) {
    extern __shared__ __align__(1024) uint8_t smem[];
    const uint32_t sbase = SBASE + ((blockIdx.x & 1) << 24);
    if (smem_u32(smem) != sbase) __trap();
    const uint32_t bars = sbase + BAR_OFF;
    const int tid = threadIdx.x, lane = tid & 31;
    const int wg = __shfl_sync(0xffffffffu, tid >> 7, 0), warp = __shfl_sync(0xffffffffu, (tid >> 5) & 3, 0);
    if (tid < 96) {
        const int row = tid >> 2, bx = blockIdx.x & 127;
        const __nv_bfloat16* p = tid < 64 ? x : (tid < 80 ? Bre : Bim);
        pf_line(p + (tid < 64 ? bx * 16 + row : (bx >> 4) * 128 + (bx & 15) * 4 + (row & 3)) * 1024 + (tid & 3) * 64);
    }
    if (wg == 4 && warp == 1 && elect_one()) {
        asm volatile("prefetch.tensormap [%0];" :: "l"(&mp.BB) : "memory");
        asm volatile("prefetch.tensormap [%0];" :: "l"(&mp.X) : "memory");
        asm volatile("prefetch.tensormap [%0];" :: "l"(&mp.Xr) : "memory");
        for (int s = 0; s < RING; s++) mbar_init(EMPTY(s), 4);
        for (int i = 0; i < 14; i++) mbar_init(XB + 8 * i, i == 3 ? 129 : (i == 4 ? 2 : (i == 5 ? 8 : 1)));
        sts32(sbase + SACT_OFF, 0u);
        asm volatile("fence.mbarrier_init.release.cluster;" ::: "memory");
        fence_async();
    }
    int cta = blockIdx.x;
    {
        unsigned int smid;
        asm volatile("mov.u32 %0, %%smid;" : "=r"(smid));
        if (full) {
            const int t = smid >> 1, u = (t - 32) / 7;
            const int g = t < 32 ? (t & 7) : (t < 60 ? t - 31 - 7 * u : 0), idx = t < 32 ? (t >> 3) : (t < 60 ? 4 + u : t - 58);
            const int lg = (0x73216540 >> (4 * g)) & 7;
            cta = ((t & ~1) == 60 || t > 65 ? 8 + 2 * t : 16 * lg + 2 * idx) + (smid & 1);
        }
    }
    const int cb = 2 * (cta >> 5) + (cta & 1), tc = (cta >> 1) & 15;
    const int db = 2 * ((cta >> 4) & 3) + (cta & 1), rc = 8 * ((cta >> 6) & 1) + ((cta >> 1) & 7);
    const long long t_start = clock64();
    if (tid >= 512 && tid < 544 && elect_one()) {
        for (int s = 0; s < RING; s++) mbar_init(FULL(s), 1);
        sts32(sbase + ROLE_OFF, cta);
        asm volatile("fence.mbarrier_init.release.cluster;" ::: "memory");
        fence_async();
        if (cta < 128) {
            #pragma unroll
            for (int s = 0; s < RING; s++) {
                mbar_expect_tx(FULL(s), STGB);
                tma_load_4d(sbase + s * STGB, &mp.BB, s * 64, cb * 16, FULL(s));
                tma_load_3d(sbase + s * STGB + 16384, &mp.X, s * 64, tc * 8, 0, FULL(s));
                tma_load_3d(sbase + s * STGB + 24576, &mp.X, s * 64, tc * 8, 8, FULL(s));
            }
        }
    }
    if (cta >= NCTA) __trap();
    __syncthreads();
    asm volatile("barrier.cluster.arrive.relaxed.aligned;" ::: "memory");
    if (wg >= 2 || cta >= 128) asm volatile("barrier.cluster.wait.acquire.aligned;" ::: "memory");
    if (wg == 4) {
        asm volatile("setmaxnreg.dec.sync.aligned.u32 24;");
        if (warp == 0) {
            const int prole = __shfl_sync(0xffffffffu, peer_role(sbase + ROLE_OFF), 0);
            const uint32_t rk = blockIdx.x & 1;
            if (cta >= 128) bar_arrive_n(DBAR + (prole >> 30), 64);
            const uint8_t* hs = reinterpret_cast<const uint8_t*>(g_h) + rc * 32 * 16384;
            if (cta < 128 && __all_sync(0xffffffffu, prole == (cta ^ 1))) {
                produce(mp, sbase, rk, cb, tc, db, rc);
            } else if (cta < 128) {
                uint32_t nw = 0;
                if (elect_one()) {
                    #pragma unroll 1
                    for (int it = RING; it < 64; it++) {
                        const int s = it % RING;
                        const uint32_t sa = sbase + s * STGB;
                        if (prole >= 128) mbar_arrive2(EMPTY(s));
                        mbar_wait_n(EMPTY(s), ((it / RING) - 1) & 1, nw);
                        mbar_expect_tx(FULL(s), STGB);
                        if (it < 32) {
                            tma_load_4d(sa, &mp.BB, (it & 15) * 64, cb * 16 + (it >> 4) * 8, FULL(s));
                            tma_load_3d(sa + 16384, &mp.X, (it & 15) * 64, tc * 8, 0, FULL(s));
                            tma_load_3d(sa + 24576, &mp.X, (it & 15) * 64, tc * 8, 8, FULL(s));
                        } else {
                            const CUtensorMap* cm = (it & 8) ? &mp.Cim : &mp.Cre;
                            tma_load_5d(sa + 16384, cm, (it & 7) * 128 + (it & 16) * 4, db * 4, FULL(s));
                            tma_load_5d(sa + 24576, cm, (it & 7) * 128 + (it & 16) * 4, db * 4 + 32, FULL(s));
                            mbar_wait_n(HOK((it >> 3) & 3), 0, nw);
                            bulk_load(sa, hs + (it - 32) * 16384, 16384, FULL(s));
                        }
                    }
                }
            } else if (cta >= 128 && prole < 128 && lane == 0) {
                mbar_arrive2(EMPTY(RING - 1));
                #pragma unroll 1
                for (int p = 0; p < 8; p++) mbar_wait(EMPTY(RING - 1), p & 1);
            }
        } else if (warp == 1) {
            if (cta < 130) {
                #pragma unroll 1
                for (int i = lane; i < 128; i += 32) {
                    const int p = (cb & 7) * 128 + i;
                    const float dt = bf16r(expf(__bfloat162float(log_dt[p]))), lr = __bfloat162float(lam_re[p]), li = __bfloat162float(lam_im[p]);
                    const float er = expf(dt * lr), den = lr * lr + li * li;
                    float sn, cs; sincospif(dt * li * 0.31830988618379067154f, &sn, &cs);
                    cs *= er; sn *= er;
                    sts128(sbase + LAM_OFF + i * 16, __float_as_uint(cs), __float_as_uint(swp ? -sn : sn),
                           __float_as_uint(__fdividef((cs - 1.f) * lr + sn * li, den)), __float_as_uint(__fdividef(sn * lr - (cs - 1.f) * li, den)));
                    float2 l = make_float2(cs, swp ? -sn : sn);
                    l = cmul(l, l); l = cmul(l, l); l = cmul(l, l); l = cmul(l, l);
                    const float2 l2 = cmul(l, l);
                    sts128(sbase + LAM_OFF + 2048 + i * 16, __float_as_uint(l.x), __float_as_uint(l.y), __float_as_uint(l2.x), __float_as_uint(l2.y));
                }
                __syncwarp();
                if (lane == 0) mbar_arrive(EPB);
                mbar_wait(EPB, 0);
                const unsigned int epoch = lds32(sbase + EPO_OFF);
                const bool one = elect_one();
                if (one) {
                    while (clock64() - t_start < TTAB) { __nanosleep(100); }
                    mbar_expect_tx(X1B(0), 16384 + 2048 + 10240);
                    bulk_load(sbase + B16F_OFF, g_img.b16f, 2048, X1B(0));
                    bulk_load(sbase + R2, cta < 2 ? g_img.m4re[cta] : g_img.h[cta & 1].m4, 8192, X1B(0));
                    bulk_load(sbase + R2 + 8192, g_img.h[cta & 1].b16i, 2048, X1B(0));
                }
                __syncwarp();
                if (cta < 128) bar_sync_n(GBAR, 288);
                if (one) {
                    if (cta < 128) { red_release(&g_cnt1); }
                    mbar_expect_tx(X1B(1), 16384);
                    wait_counter(&g_cnt1, 128u * epoch);
                    #pragma unroll 1
                    for (int i = 0; i < 4; i++) { bulk_load(sbase + R1 + i * 8192, g_X1 + (cta & 127) * 2048 + i * 512, 8192, X1B(i >> 1)); delay(PCL); }
                }
                #pragma unroll 1
                for (int i = 0; i < 4; i++) {
                    if (one) load_w(mp.W, sbase, cta, i);
                    __syncwarp();
                    if (i != 2) bar_sync_n(LBAR + min(i, 2), 160);
                }
                if (one) {
                    red_release(cta < 128 ? &g_cnt2 : &g_cnt3);
                    if (cta < 128) {
                        const uint8_t* img = reinterpret_cast<const uint8_t*>(g_X2) + (8 * rc + db) * X2_IMG;
                        mbar_expect_tx(ZOK, 32768 - 256);
                        wait_counter(&g_cnt2, 128u * epoch);
                        bulk_load(sbase + R1 + 1152, img + 1152, 15232, ZOK);
                        bulk_load(sbase + R1 + 16384 + 1152, img + X2_IMG / 2 + 1152, 15232, ZOK);
                        bulk_load(sbase + R1, img, 1024, ZOK);
                        bulk_load(sbase + R1 + 16384, img + X2_IMG / 2, 1024, ZOK);
                    }
                }
            }
        } else if (warp == 2) {
            if (cta < 128) {
                const uint8_t* bp = reinterpret_cast<const uint8_t*>((lane & 16) ? Bim : Bre) + (cb * 128 + tc * 4 + ((lane >> 2) & 3)) * 2048 + (lane & 3) * 128;
                if (elect_one()) {
                    mbar_expect_tx(XB, 32768 + 256);
                    bulk_load(sbase + GATE_OFF, gate_w + db * 64, 128, XB);
                    bulk_load(sbase + GATE_OFF + 128, gate_w + db * 64 + 512, 128, XB);
                    #pragma unroll
                    for (int i = 0; i < 8; i++) tma_load_2d(sbase + R0 + i * 4096, &mp.Xr, rc * 1024 + db * 64 + (i >> 2) * 512, (i & 3) * 32, XB);
                }
                __syncwarp();
                pf_line(bp + 1024); pf_line(bp + 1536);
                if ((cta & 63) < 12) pf_line(reinterpret_cast<const uint8_t*>(&g_img) + (cta & 63) * 4096 + lane * 128);
                while (clock64() - t_start < PFW) { }
                const uint32_t wrow = (((cta & 1) ? 128 - (cta >> 1) : (cta >> 1)) + 128 * (lane >> 1)) & 2047;
                const uint8_t* wp = reinterpret_cast<const uint8_t*>(lane & 1 ? w_i : w_r) + wrow * 1026u;
                #pragma unroll 1
                for (int k = 0; k < 9; k++) { pf_line(wp + (k < 8 ? k * 128 : 1024)); __nanosleep(200); }
                while (clock64() - t_start < PFB) { }
                #pragma unroll 1
                for (int k = 0; k < 16; k += 4) { pf_line(bp + 64 * 2048 + k * 128); __nanosleep(200); }
                const uint8_t* cp = reinterpret_cast<const uint8_t*>((lane & 16) ? Cim : Cre) + (cta * 8 + (lane & 7)) * 2048 + (lane & 8) * 32;
                #pragma unroll 1
                for (int k = 0; k < 8; k++) {
                    while (clock64() - t_start < PFC + k * PFCS) { __nanosleep(100); }
                    pf_line(cp + (k & 3) * 512 + (k >> 2) * 128);
                }
            }
        } else {
            unsigned int epoch = 0;
            if (cta >= 128) bar_sync_n(DBAR, 64);
            if (lane == 0) {
                epoch = atomicAdd(&g_ticket, 1u);
                epoch = (full ? epoch / NCTA : epoch / 130u) + 1u;
                sts32(sbase + EPO_OFF, epoch);
                mbar_arrive(EPB);
            }
            __syncwarp();
            if (cta < 128) {
                #pragma unroll 1
                for (int i = 0; i < 4; i++) {
                    bar_sync_n(HBAR + i, 160);
                    if (lane == 0) {
                        red_release(&g_cnth(i));
                        wait_counter(&g_cnth(i), 128u * epoch);
                        mbar_arrive(HOK(i));
                    }
                    __syncwarp();
                }
                if (lane == 0) {
                    mbar_expect_tx(XB, 32768);
                    #pragma unroll 1
                    for (int i = 0; i < 8; i++) { tma_load_2d(sbase + R0 + i * 4096, &mp.Xr, rc * 1024 + db * 64 + (i >> 2) * 512, (i & 3) * 32, XB); __nanosleep(150); }
                }
            } else if (cta >= 130 && lane == 0) {
                #pragma unroll 1
                for (int i = 0; i < (1 << 22); i++) {
                    __nanosleep(200);
                    if ((int)(*reinterpret_cast<volatile unsigned int*>(&g_ticket) - NCTA * epoch) >= 0) break;
                }
            }
        }
    } else if (wg >= 2) {
      if (cta < 128) {
          float2 w1, w32;
          sincospif((float)(16 * tid128() + rc) * (1.f / 1024.f), &w1.y, &w1.x);
          w32 = cmul(w1, w1); w32 = cmul(w32, w32); w32 = cmul(w32, w32); w32 = cmul(w32, w32); w32 = cmul(w32, w32);
          gen_dft(sbase + R1, tid128(), w1, wg == 2 ? make_float2(1.f, 0.f) : make_float2(w32.x, -w32.y), 4 * wg - 8, 4 * wg - 4, 0.5f);
          fence_async();
          bar_sync_n(wg, 128);
          mbar_wait(XB, 0);
          fft_p1(sbase, bars, wg - 2, rc, db, (uint32_t)t_start + P1END);
          bar_arrive_n(GBAR, 288);
      }
      if (wg == 3) {
        asm volatile("setmaxnreg.inc.sync.aligned.u32 120;");
        {
            if (cta < 128) {
                mbar_wait(EPB, 0);
                #pragma unroll 1
                for (int half = 0; half < 2; half++) {
                    const int t1 = tid128(), ch = t1 >> 1, hf = t1 & 1, p = cb * 128 + half * 64 + ch;
                    if (half) {
                        mbar_wait(X1B(0), 0);
                        float s = 0.f;
                        #pragma unroll
                        for (int i = 0; i < 16; i++) s += __ldcg(&g_gp[(16 * rc + i) * 128 + t1]);
                        const float gv = bf16r(__fdividef(1.f, 1.f + expf(-bf16r(s))));
                        sts32(sbase + GATE_OFF + 4 * t1, pack2(gv, 1.f - gv));
                    }
                    const uint4 pm = lds128(sbase + LAM_OFF + (half * 64 + ch) * 16);
                    const uint32_t sg = (uint32_t)swp << 31;
                    float2 lam = make_float2(__uint_as_float(pm.x), __uint_as_float(pm.y ^ sg));
                    float cr = __uint_as_float(pm.z), ci = __uint_as_float(pm.w);
                    const uint4 pp = lds128(sbase + LAM_OFF + 2048 + (half * 64 + ch) * 16);
                    const float2 l16 = make_float2(__uint_as_float(pp.x), __uint_as_float(pp.y ^ sg)), l32 = make_float2(__uint_as_float(pp.z), __uint_as_float(pp.w ^ sg));
                    const float2 l64 = cmul(l32, l32), l128 = cmul(l64, l64), l256 = cmul(l128, l128);
                    const unsigned int par = lds32(sbase + EPO_OFF) & 1u;
                    if (__float_as_uint(l256.x) == 0x9e3779b9u) sts32(sbase + SACT_OFF + 4, 0u);
                    bar_sync_n(DBAR, 384);
                    uint2 ur[16], ui[16];
                    #pragma unroll
                    for (int r = 15; r >= 0; r--) { ur[r] = lds64(sbase + R0 + r * 1024 + t1 * 8); ui[r] = lds64(sbase + R0 + 16384 + r * 1024 + t1 * 8); }
                    float2 e[4], E0;
                    e[0] = make_float2(bflo(ur[15].x), bflo(ui[15].x));
                    e[1] = cfma(l16, e[0], make_float2(bfhi(ur[15].x), bfhi(ui[15].x)));
                    e[2] = cfma(l16, e[1], make_float2(bflo(ur[15].y), bflo(ui[15].y)));
                    e[3] = cfma(l16, e[2], make_float2(bfhi(ur[15].y), bfhi(ui[15].y)));
                    E0.x = __shfl_xor_sync(0xffffffffu, e[3].x, 1); E0.y = __shfl_xor_sync(0xffffffffu, e[3].y, 1);
                    const uint2* src = reinterpret_cast<const uint2*>(g_agg) + (tc - 1 - hf) * P_DIM + p;
                    const int nv = tc - hf;
                    uint2 v[8];
                    {
                        const bf2 c2 = asbf2(pack2(cr, cr)), n2 = asbf2(pack2(-cr, -cr)), s2 = asbf2(pack2(-ci, -ci));
                        #pragma unroll
                        for (int r = 15; r >= 0; r--) {
                            if (r == 8) {
                                boundary();
                                #pragma unroll
                                for (int i = 0; i < 8; i++) {
                                    v[i] = make_uint2(par, par);
                                    if (2 * i < nv) asm volatile("ld.relaxed.gpu.global.v2.u32 {%0, %1}, [%2];" : "=r"(v[i].x), "=r"(v[i].y) : "l"(src - i * 2 * P_DIM) : "memory");
                                }
                                #pragma unroll
                                for (int q = r; q >= 0; q--) asm volatile("" : "+r"(ur[q].x), "+r"(ur[q].y), "+r"(ui[q].x), "+r"(ui[q].y) :: "memory");
                            }
                            const bf2 a = asbf2(ur[r].x), b = asbf2(ui[r].x), c = asbf2(ur[r].y), d = asbf2(ui[r].y);
                            ur[r].x = asu32(__hfma2(c2, a, __hmul2(s2, b))); ui[r].x = asu32(__hfma2(n2, b, __hmul2(s2, a)));
                            ur[r].y = asu32(__hfma2(c2, c, __hmul2(s2, d))); ui[r].y = asu32(__hfma2(n2, d, __hmul2(s2, c)));
                            asm volatile("" : "+r"(ur[r].x), "+r"(ur[r].y), "+r"(ui[r].x), "+r"(ui[r].y) :: "memory");
                        }
                    }
                    __syncwarp();
                    if (lane == 0) mbar_arrive2(R0F);
                    #pragma unroll 1
                    for (int spins = 0; spins < (1 << 20); spins++) {
                        uint32_t bad = 0;
                        #pragma unroll
                        for (int i = 0; i < 8; i++) bad |= (v[i].x ^ par) | (v[i].y ^ par);
                        if (!__any_sync(0xffffffffu, bad & 1u)) break;
                        #pragma unroll
                        for (int i = 0; i < 8; i++)
                            if (2 * i < nv) asm volatile("ld.relaxed.gpu.global.v2.u32 {%0, %1}, [%2];" : "+r"(v[i].x), "+r"(v[i].y) : "l"(src - i * 2 * P_DIM) : "memory");
                    }
                    if (t1 == 0) { sts32(sbase + SACT_OFF, 1u); }
                    float2 H = make_float2(__uint_as_float(v[7].x), __uint_as_float(v[7].y));
                    #pragma unroll
                    for (int i = 6; i >= 0; i--) H = cfma(l256, H, make_float2(__uint_as_float(v[i].x), __uint_as_float(v[i].y)));
                    if (hf) H = cmul(H, l128);
                    H.x += __shfl_xor_sync(0xffffffffu, H.x, 1); H.y += __shfl_xor_sync(0xffffffffu, H.y, 1);
                    float2 st[4];
                    st[0] = hf ? cfma(l64, H, E0) : H;
                    st[1] = cfma(l16, st[0], e[0]); st[2] = cfma(l32, st[0], e[1]); st[3] = cfma(l16, cmul(l32, st[0]), e[2]);
                    const bf2 gr0 = asbf2(pack2(cr * st[0].x - ci * st[0].y, cr * st[1].x - ci * st[1].y)), gr1 = asbf2(pack2(cr * st[2].x - ci * st[2].y, cr * st[3].x - ci * st[3].y));
                    const bf2 gi0 = asbf2(pack2(-ci * st[0].x - cr * st[0].y, -ci * st[1].x - cr * st[1].y)), gi1 = asbf2(pack2(-ci * st[2].x - cr * st[2].y, -ci * st[3].x - cr * st[3].y));
                    uint2* dst = reinterpret_cast<uint2*>(g_h + (half * 16 + cb) * 1024 + tc * 64) + t1;
                    lam.y = -lam.y;
                    float2 z = lam;
                    uint32_t pw[16], tp = clk32() + warp * (PCR / 2);
                    #pragma unroll
                    for (int r = 0; r < 16; r++) {
                        pw[r] = pack2(z.x, z.y); z = cmul(z, lam);
                        const bf2 pr = __low2bfloat162(asbf2(pw[r])), pi = __high2bfloat162(asbf2(pw[r]));
                        if (!(r & 1)) pace(tp, 2 * PCR);
                        __stcg(dst + r * 65536, make_uint2(asu32(__hfma2(pr, gr0, __hfma2(pi, neg2(gi0), asbf2(ur[r].x)))), asu32(__hfma2(pr, gr1, __hfma2(pi, neg2(gi1), asbf2(ur[r].y))))));
                    }
                    bar_arrive_n(HBAR + 2 * half, 160);
                    if (t1 == 0) { sts32(sbase + SACT_OFF, 0u); }
                    #pragma unroll
                    for (int r = 0; r < 16; r++) {
                        const bf2 pr = __low2bfloat162(asbf2(pw[r])), pi = __high2bfloat162(asbf2(pw[r]));
                        if (!(r & 1)) pace(tp, 2 * PCH);
                        __stcg(dst + r * 65536 + 16384, make_uint2(asu32(__hfma2(pr, gi0, __hfma2(pi, gr0, asbf2(ui[r].x)))), asu32(__hfma2(pr, gi1, __hfma2(pi, gr1, asbf2(ui[r].y))))));
                    }
                    bar_arrive_n(HBAR + 2 * half + 1, 160);
                }
            }
        }
      } else {
        asm volatile("setmaxnreg.inc.sync.aligned.u32 144;");
        if (cta < 130) {
            fft_p2(sbase, bars, cta, w_r, w_i);
            bar_sync_n(LBAR + 2, 160);
            if (cta < 128) {
                const int j = tid128();
                if (j < 16) {
                    const uint2 d0 = __ldg(reinterpret_cast<const uint2*>(dskip) + db * 16 + j), d1 = __ldg(reinterpret_cast<const uint2*>(dskip) + db * 16 + 128 + j);
                    sts128(sbase + DSK_OFF + j * 16, d0.x, d0.y, d1.x, d1.y);
                }
                mbar_wait(HOK(2), 0);
                const float gv = bflo(lds32(sbase + GATE_OFF + 4 * j));
                gen_dft(sbase + R2, j, cis(16 * j + rc), make_float2(gv * (1.f / 1048576.f), 0.f), 0, 8, gv * (1.f / 1048576.f));
                const uint8_t* img = reinterpret_cast<const uint8_t*>(g_X2) + (8 * rc + db) * X2_IMG;
                if ((j >> 4) == 4) {
                    wait_counter(&g_cnt3, 2u * lds32(sbase + EPO_OFF));
                    const float cs = g_img.cs[0][4 * rc][0], sn = g_img.cs[0][4 * rc][1];
                    const uint4* s4 = reinterpret_cast<const uint4*>(img + ((j >> 3) & 1) * (X2_IMG / 2) + 16384) + (j & 7);
                    const uint4 a = __ldcg(s4), b = __ldcg(s4 + 64);
                    sts128(sbase + R1 + ((j >> 3) & 1) * 16384 + 1024 + (j & 7) * 16,
                           pack2(cs * bflo(a.x) - sn * bflo(b.x), cs * bfhi(a.x) - sn * bfhi(b.x)), pack2(cs * bflo(a.y) - sn * bflo(b.y), cs * bfhi(a.y) - sn * bfhi(b.y)),
                           pack2(cs * bflo(a.z) - sn * bflo(b.z), cs * bfhi(a.z) - sn * bfhi(b.z)), pack2(cs * bflo(a.w) - sn * bflo(b.w), cs * bfhi(a.w) - sn * bfhi(b.w)));
                }
                fence_async();
                mbar_arrive(ZOK);
            }
        }
      }
    } else {
        if (cta < 128) {
            {
                const int w8 = tid >> 5;
                if (w8 == 0) pf_line(((lane & 16) ? Bim : Bre) + (cb * 128 + tc * 4 + ((lane >> 2) & 3)) * 1024 + (4 + (lane & 3)) * 64);
                else if (w8 < 3) pf_line(x + (cta * 16 + (lane >> 1)) * 1024 + (2 + 2 * w8 + (lane & 1)) * 64);
            }
            float A[64];
            #pragma unroll
            for (int i = 0; i < 64; i++) A[i] = 0.f;
            gemm_main(A, sbase, wg, warp, lane, cb, tc, swp);
            const int ln = tid128() & 31, row = 64 * wg + 16 * warp + (ln >> 2);
            if (wg == 0) bar_arrive_n(TBAR, 256);
            mbar_wait(ZOK, 0);
            float om[2];
            om[0] = bfhi(lds32(sbase + GATE_OFF + 4 * row)); om[1] = bfhi(lds32(sbase + GATE_OFF + 4 * row + 32));
            wgmma_wait<0>();
            reg_fence<64>(A);
            #pragma unroll
            for (int i = 0; i < 32; i++) { const float o = om[(i >> 1) & 1], t = o * A[i], u = A[i + 32]; A[i] = fmaf(o, u, t); A[i + 32] = fmaf(-o, u, t); }
            constexpr uint32_t s16 = SBASE / 16;
            wgmma_fence();
            #pragma unroll
            for (int ks = 0; ks < 8; ks++)
                ss128<0, 1>(A, mkd(s16 + wg * 512, R2 + (ks >> 2) * 16384 + (ks & 3) * 32, 16, 1024, 1), mkd(s16, R1 + ks * 2048, 16384, 1024, 1));
            wgmma_commit();
            if (wg == 0) bar_arrive_n(TBAR + 1, 256);
            float* o = out + (size_t)(16 * row + rc) * 1024 + db * 64 + 4 * (ln & 3);
            mbar_wait(XB, 1);
            wgmma_wait<0>();
            reg_fence<64>(A);
            #pragma unroll
            for (int J = 0; J < 4; J++) {
                if (J) boundary();
                const uint4 dk = lds128(sbase + DSK_OFF + (4 * J + (ln & 3)) * 16);
                #pragma unroll
                for (int h = 0; h < 2; h++) {
                    const uint32_t xo = sbase + R0 + (row + 8 * h) * 128 + (ln & 1) * 8 + (((2 * J + ((ln >> 1) & 1)) ^ (ln >> 2)) << 4);
                    uint2 p = lds64(xo), s = lds64(xo + 16384);
                    p.x = hmul2bf(p.x, dk.x); p.y = hmul2bf(p.y, dk.y); s.x = hmul2bf(s.x, dk.z); s.y = hmul2bf(s.y, dk.w);
                    const float* a = A + 8 * J + 2 * h;
                    float4 u = make_float4(fmaf(om[h], bflo(p.x), a[0] + a[32]), fmaf(om[h], bfhi(p.x), a[1] + a[33]), fmaf(om[h], bflo(p.y), a[4] + a[36]), fmaf(om[h], bfhi(p.y), a[5] + a[37]));
                    float4 v = make_float4(fmaf(om[h], bflo(s.x), a[0] - a[32]), fmaf(om[h], bfhi(s.x), a[1] - a[33]), fmaf(om[h], bflo(s.y), a[4] - a[36]), fmaf(om[h], bfhi(s.y), a[5] - a[37]));
                    __stcs(reinterpret_cast<float4*>(o + h * 131072 + J * 16), u);
                    __stcs(reinterpret_cast<float4*>(o + h * 131072 + J * 16 + 512), v);
                }
            }
        }
    }
}

typedef CUresult (*PFN_encodeTiled_t)(CUtensorMap*, CUtensorMapDataType, cuuint32_t, void*, const cuuint64_t*, const cuuint64_t*,
                                      const cuuint32_t*, const cuuint32_t*, CUtensorMapInterleave, CUtensorMapSwizzle,
                                      CUtensorMapL2promotion, CUtensorMapFloatOOBfill);

static CUresult make_map(PFN_encodeTiled_t enc, CUtensorMap* m, int rank, const void* ptr, const cuuint64_t* dims, const cuuint64_t* strides, const cuuint32_t* box) {
    cuuint32_t es[5] = {1, 1, 1, 1, 1};
    return enc(m, CU_TENSOR_MAP_DATA_TYPE_BFLOAT16, rank, (void*)ptr, dims, strides, box, es, CU_TENSOR_MAP_INTERLEAVE_NONE, CU_TENSOR_MAP_SWIZZLE_128B,
        CU_TENSOR_MAP_L2_PROMOTION_L2_128B, CU_TENSOR_MAP_FLOAT_OOB_FILL_NONE);
}
static void make_map_2d(PFN_encodeTiled_t enc, CUtensorMap* m, const void* ptr, int rows, int cols, int box_rows) {
    cuuint64_t dims[2] = {(cuuint64_t)cols, (cuuint64_t)rows};
    cuuint64_t strides[1] = {(cuuint64_t)cols * 2};
    cuuint32_t box[2] = {64, (cuuint32_t)box_rows};
    make_map(enc, m, 2, ptr, dims, strides, box);
}

extern "C" void kernel_launch(void* const* d_in, const int* in_sizes, int n_in, void* d_out, int out_size) {
    const __nv_bfloat16* x = (const __nv_bfloat16*)d_in[0];
    const __nv_bfloat16* w_r = (const __nv_bfloat16*)d_in[1];
    const __nv_bfloat16* w_i = (const __nv_bfloat16*)d_in[2];
    const __nv_bfloat16* lam_re = (const __nv_bfloat16*)d_in[4];
    const __nv_bfloat16* lam_im = (const __nv_bfloat16*)d_in[5];
    const __nv_bfloat16* B_re = (const __nv_bfloat16*)d_in[6];
    const __nv_bfloat16* B_im = (const __nv_bfloat16*)d_in[7];
    const __nv_bfloat16* C_re = (const __nv_bfloat16*)d_in[8];
    const __nv_bfloat16* C_im = (const __nv_bfloat16*)d_in[9];
    const __nv_bfloat16* log_dt = (const __nv_bfloat16*)d_in[10];
    const __nv_bfloat16* dskip = (const __nv_bfloat16*)d_in[11];
    const __nv_bfloat16* gate_w = (const __nv_bfloat16*)d_in[12];

    static PFN_encodeTiled_t enc = nullptr;
    static Maps mp;
    static int grid = 130, swp = 0, copyB = 0;
    static void* bcopy = nullptr;
    static const void* key[7] = {nullptr, nullptr, nullptr, nullptr, nullptr, nullptr, nullptr};
    if (!enc) {
        cudaDriverEntryPointQueryResult qres;
        cudaGetDriverEntryPoint("cuTensorMapEncodeTiled", (void**)&enc, cudaEnableDefault, &qres);
        cudaFuncSetAttribute(fused_kernel<true>, cudaFuncAttributeMaxDynamicSharedMemorySize, TOT_SMEM);
        cudaFuncSetAttribute(fused_kernel<false>, cudaFuncAttributeMaxDynamicSharedMemorySize, TOT_SMEM);
        int dev = 0, nsm = 0;
        cudaGetDevice(&dev);
        cudaDeviceGetAttribute(&nsm, cudaDevAttrMultiProcessorCount, dev);
        grid = nsm == NCTA ? NCTA : 130;
    }
    if (key[0] != x || key[1] != B_re || key[2] != B_im || key[3] != C_re || key[4] != C_im || key[5] != w_r || key[6] != w_i) {
        cudaGetSymbolAddress(&bcopy, g_Bcopy);
        {
            const uintptr_t a = (uintptr_t)B_re, b = (uintptr_t)B_im;
            swp = b < a;
            cuuint64_t dims[4] = {D_DIM, 8, 2, P_DIM / 8};
            cuuint64_t strides[3] = {D_DIM * 2, (cuuint64_t)(swp ? a - b : b - a), D_DIM * 2 * 8};
            cuuint32_t box[4] = {64, 8, 2, 8};
            copyB = strides[1] == 0 || (strides[1] & 15) || strides[1] >= (1ull << 39);
            if (!copyB) copyB = make_map(enc, &mp.BB, 4, swp ? B_im : B_re, dims, strides, box) != CUDA_SUCCESS;
            if (copyB) {
                swp = 0; strides[1] = (cuuint64_t)P_DIM * D_DIM * 2;
                make_map(enc, &mp.BB, 4, bcopy, dims, strides, box);
            }
        }
        {
            cuuint64_t dims[3] = {D_DIM, S_LEN / 16, 16};
            cuuint64_t strides[2] = {D_DIM * 2 * 16, D_DIM * 2};
            cuuint32_t box[3] = {64, 8, 8};
            make_map(enc, &mp.X, 3, x, dims, strides, box);
        }
        make_map_2d(enc, &mp.Xr, x, S_LEN / 16, D_DIM * 16, 32);
        {
            cuuint64_t dims[5] = {P_DIM, 2, 4, 2, D_DIM / 16};
            cuuint64_t strides[4] = {P_DIM * 2, P_DIM * 2 * 4, P_DIM * 2 * 2, P_DIM * 2 * 16};
            cuuint32_t box[5] = {64, 2, 4, 2, 4};
            make_map(enc, &mp.Cre, 5, C_re, dims, strides, box);
            make_map(enc, &mp.Cim, 5, C_im, dims, strides, box);
        }
        for (int a = 0; a < 2; a++) {
            cuuint64_t dims[3] = {128 * 513 - 448, 8, 16};
            cuuint64_t strides[2] = {128, 128 * 513 * 2};
            cuuint32_t box[3] = {64, 8, 4};
            make_map(enc, &mp.W[a], 3, a ? w_i : w_r, dims, strides, box);
        }
        key[5] = w_r; key[6] = w_i;
        key[0] = x; key[1] = B_re; key[2] = B_im; key[3] = C_re; key[4] = C_im;
    }
    if (copyB) {
        cudaMemcpyAsync(bcopy, B_re, (size_t)P_DIM * D_DIM * 2, cudaMemcpyDeviceToDevice, cudaStreamPerThread);
        cudaMemcpyAsync((char*)bcopy + (size_t)P_DIM * D_DIM * 2, B_im, (size_t)P_DIM * D_DIM * 2, cudaMemcpyDeviceToDevice, cudaStreamPerThread);
    }
    (grid == NCTA ? fused_kernel<true> : fused_kernel<false>)<<<grid, 640, TOT_SMEM, cudaStreamPerThread>>>(x, B_re, B_im, swp, w_r, w_i, lam_re, lam_im, log_dt, dskip, gate_w,
        C_re, C_im, (float*)d_out, mp);
}
```

```cpp
#include <cuda_runtime.h>
#include <cuda_bf16.h>
#include <cuda.h>
#include <stdint.h>

#define S_LEN 2048
#define D_DIM 1024
#define P_DIM 1024

namespace ct {
constexpr double PI = 3.14159265358979323846264338327950288;
constexpr double tsin(double x) { double term = x, sum = x; for (int i = 1; i < 12; i++) { term *= -x * x / ((2 * i) * (2 * i + 1)); sum += term; } return sum; }
constexpr double tcos(double x) { double term = 1, sum = 1; for (int i = 1; i < 12; i++) { term *= -x * x / ((2 * i - 1) * (2 * i)); sum += term; } return sum; }
struct CosTab { double v[513]; };
constexpr CosTab make_cos() {
    CosTab t{};
    for (int m = 0; m <= 512; m++) t.v[m] = m == 512 ? 0.0 : (m <= 256 ? tcos(2 * PI * m / 2048.0) : tsin(2 * PI * (512 - m) / 2048.0));
    return t;
}
constexpr CosTab COS = make_cos();
constexpr double cos2048(int m) {
    m &= 2047;
    if (m > 1024) m = 2048 - m;
    if (m > 512) return -COS.v[1024 - m];
    return COS.v[m];
}
constexpr double sin2048(int m) { return cos2048(m - 512); }
constexpr unsigned short bf16bits(double v) {
    if (v == 0.0) return 0;
    unsigned short s = 0;
    if (v < 0) { s = 0x8000; v = -v; }
    int e = 0;
    while (v >= 2.0) { v *= 0.5; e++; }
    while (v < 1.0) { v *= 2.0; e--; }
    double r = v * 128.0;
    int ri = (int)r;
    double fr = r - ri;
    if (fr > 0.5 || (fr == 0.5 && (ri & 1))) ri++;
    if (ri == 256) { ri = 128; e++; }
    return (unsigned short)(s | ((e + 127) << 7) | (ri - 128));
}
constexpr int kmaj(int row, int k, int sbo) { return ((row >> 3) * sbo + (k >> 3) * 128 + (row & 7) * 16 + (k & 7) * 2) >> 1; }
constexpr double rot(int ro, int ri, int a) { return ro == ri ? cos2048(a) : (ro == 0 ? sin2048(a) : -sin2048(a)); }
constexpr int bin(int n) { return (n & 8) | ((n & 3) << 1) | ((n >> 2) & 1); }
constexpr int bout(int n) { return ((n & 2) << 2) | ((n >> 1) & 6) | (n & 1); }
struct Half {
    unsigned short m4[4096];
    unsigned short b16i[1024];
    unsigned short tw[2][128][8];
};
struct Img { unsigned short b16f[1024]; Half h[2]; float cs[16][128][2]; unsigned short m4re[2][4096]; };
constexpr Img make_img() {
    Img t{};
    for (int n = 0; n < 32; n++) for (int k = 0; k < 32; k++) t.b16f[kmaj(n, k, 512)] = bf16bits(rot(((n >> 4) ^ (n >> 3)) & 1, k >> 4, bin(k & 15) * (n & 15) * 128));
    for (int r = 0; r < 16; r++) for (int j = 0; j < 128; j++) { t.cs[r][j][0] = (float)cos2048(16 * j + r); t.cs[r][j][1] = (float)sin2048(16 * j + r); }
    for (int ke = 0; ke < 2; ke++) {
        Half& h = t.h[ke];
        for (int n = 0; n < 32; n++) for (int k = 0; k < 32; k++) h.b16i[kmaj(n, k, 512)] = bf16bits(rot(n >> 4, ((k >> 4) ^ (k >> 3)) & 1, -bout(n & 15) * (k & 15) * 128));
        for (int m = 0; m < 64; m++) for (int k = 0; k < 64; k++) {
            int a = 4 * (m >> 3) + (m & 3), ro = (m >> 2) & 1, kx = 8 * (k >> 4) + (k & 7), ri = (k >> 3) & 1;
            h.m4[kmaj(m, k, 1024)] = bf16bits(rot(ro, ri, -a * (ke + 2 * kx) * 32));
            t.m4re[ke][kmaj(m, k, 1024)] = ro ? 0 : h.m4[kmaj(m, k, 1024)];
        }
        for (int tid = 0; tid < 128; tid++) {
            int kap = ke + 2 * (tid >> 2), q = tid & 3;
            for (int hb = 0; hb < 2; hb++) for (int e = 0; e < 2; e++) {
                int n = 8 * hb + 2 * q + e;
                h.tw[0][tid][4 * hb + e] = bf16bits(cos2048(2 * bin(n) * kap));  h.tw[0][tid][4 * hb + 2 + e] = bf16bits(-sin2048(2 * bin(n) * kap));
                h.tw[1][tid][4 * hb + e] = bf16bits(cos2048(2 * bout(n) * kap)); h.tw[1][tid][4 * hb + 2 + e] = bf16bits(sin2048(2 * bout(n) * kap));
            }
        }
    }
    return t;
}
}
__device__ __align__(128) const ct::Img g_img = ct::make_img();

#define SBASE 0x400u
#define RING 4
#define STGB 32768
#define R0 (4 * 32768)
#define R1 (5 * 32768)
#define R2 (6 * 32768)
#define B16F_OFF (7 * 32768)
#define BAR_OFF (B16F_OFF + 2048)
#define GATE_OFF (BAR_OFF + 256)
#define DSK_OFF (GATE_OFF + 512)
#define TOT_SMEM (DSK_OFF + 256)
#define NCTA 132
#define X2_IMG 36864

__device__ __align__(1024) uint4 g_X1[128 * 2048];
__device__ __align__(1024) uint4 g_X2[128 * X2_IMG / 16];
__device__ __align__(128) float g_gp[256 * 128];
__device__ __align__(1024) uint4 g_h[16 * 32 * 1024];
__device__ __align__(128) unsigned long long g_agg[16 * P_DIM];
__device__ __align__(128) unsigned int g_cnt[8 * 32];
__device__ __align__(1024) __nv_bfloat16 g_Bcopy[2 * P_DIM * D_DIM];
#define g_ticket g_cnt[0]
#define g_cnt1 g_cnt[32]
#define g_cnt2 g_cnt[64]
#define g_cnt3 g_cnt[224]
#define g_cnth(i) g_cnt[96 + 32 * (i)]


__device__ __forceinline__ float bf16r(float v) { return __bfloat162float(__float2bfloat16_rn(v)); }
__device__ __forceinline__ float2 cmul(float2 a, float2 b) { return make_float2(a.x * b.x - a.y * b.y, a.x * b.y + a.y * b.x); }
__device__ __forceinline__ float2 cfma(float2 a, float2 b, float2 c) {
    float re = fmaf(a.x, b.x, c.x); re = fmaf(-a.y, b.y, re);
    float im = fmaf(a.x, b.y, c.y); im = fmaf(a.y, b.x, im);
    return make_float2(re, im);
}
__device__ __forceinline__ uint32_t smem_u32(const void* p) { return (uint32_t)__cvta_generic_to_shared(p); }
__device__ __forceinline__ void bar_sync_n(int id, int n) { asm volatile("bar.sync %0, %1;" :: "r"(id), "r"(n) : "memory"); }
__device__ __forceinline__ void bar_arrive_n(int id, int n) { asm volatile("bar.arrive %0, %1;" :: "r"(id), "r"(n) : "memory"); }
__device__ __forceinline__ uint32_t pack2(float lo, float hi) { uint32_t r; asm("cvt.rn.bf16x2.f32 %0, %1, %2;" : "=r"(r) : "f"(hi), "f"(lo)); return r; }
__device__ __forceinline__ uint64_t mkd(uint32_t b16, uint32_t off, uint32_t lbo, uint32_t sbo, uint32_t swz = 0) {
    uint64_t d;
    asm("mov.b64 %0, {%1, %2};" : "=l"(d) : "r"(b16 + ((off >> 4) + ((lbo >> 4) << 16))), "r"((sbo >> 4) | (swz << 30)));
    return d;
}
__device__ __forceinline__ void wgmma_fence() { asm volatile("wgmma.fence.sync.aligned;" ::: "memory"); }
__device__ __forceinline__ void wgmma_commit() { asm volatile("wgmma.commit_group.sync.aligned;" ::: "memory"); }
template <int N> __device__ __forceinline__ void wgmma_wait() { asm volatile("wgmma.wait_group.sync.aligned %0;" :: "n"(N) : "memory"); }
__device__ __forceinline__ void fence_async() { asm volatile("fence.proxy.async.shared::cta;" ::: "memory"); }
template <int N> __device__ __forceinline__ void reg_fence(float* d) {
    #pragma unroll
    for (int i = 0; i < N; i++) asm volatile("" : "+f"(d[i]) :: "memory");
}
#define X16(c, d, o) c(d[o]),c(d[o+1]),c(d[o+2]),c(d[o+3]),c(d[o+4]),c(d[o+5]),c(d[o+6]),c(d[o+7]),c(d[o+8]),c(d[o+9]),c(d[o+10]),c(d[o+11]),c(d[o+12]),c(d[o+13]),c(d[o+14]),c(d[o+15])
#define RW(x) "+f"(x)
#define WO(x) "=f"(x)
#define R64(d) X16(RW, d, 0), X16(RW, d, 16), X16(RW, d, 32), X16(RW, d, 48)
#define W64(d) X16(WO, d, 0), X16(WO, d, 16), X16(WO, d, 32), X16(WO, d, 48)
#define R16(d) X16(RW, d, 0)
#define WO16(d) X16(WO, d, 0)
#define L64 "{%0,%1,%2,%3,%4,%5,%6,%7,%8,%9,%10,%11,%12,%13,%14,%15,%16,%17,%18,%19,%20,%21,%22,%23,%24,%25,%26,%27,%28,%29,%30,%31," \
        "%32,%33,%34,%35,%36,%37,%38,%39,%40,%41,%42,%43,%44,%45,%46,%47,%48,%49,%50,%51,%52,%53,%54,%55,%56,%57,%58,%59,%60,%61,%62,%63}"
#define L16 "{%0,%1,%2,%3,%4,%5,%6,%7,%8,%9,%10,%11,%12,%13,%14,%15}"

template <int TA, int TB> __device__ __forceinline__ void ss128(float* d, uint64_t a, uint64_t b) {
    asm volatile("wgmma.mma_async.sync.aligned.m64n128k16.f32.bf16.bf16 " L64 ", %64, %65, 1, 1, 1, %66, %67;\n" : R64(d) : "l"(a), "l"(b), "n"(TA), "n"(TB));
}
template <int TA, int TB> __device__ __forceinline__ void ss128_p(float* d, uint64_t a, uint64_t b, int acc) {
    asm volatile("{\n.reg .pred p;\nsetp.ne.s32 p, %68, 0;\nwgmma.mma_async.sync.aligned.m64n128k16.f32.bf16.bf16 " L64 ", %64, %65, p, 1, 1, %66, %67;\n}\n" : R64(d) : "l"(a), "l"(b), "n"(TA), "n"(TB), "r"(acc));
}
template <int TA, int TB> __device__ __forceinline__ void ss128_z(float* d, uint64_t a, uint64_t b) {
    asm volatile("wgmma.mma_async.sync.aligned.m64n128k16.f32.bf16.bf16 " L64 ", %64, %65, 0, 1, 1, %66, %67;\n" : W64(d) : "l"(a), "l"(b), "n"(TA), "n"(TB));
}
__device__ __forceinline__ void rs32(float* d, uint32_t a0, uint32_t a1, uint32_t a2, uint32_t a3, uint64_t b) {
    asm volatile("wgmma.mma_async.sync.aligned.m64n32k16.f32.bf16.bf16 " L16 ", {%16,%17,%18,%19}, %20, 1, 1, 1, 0;\n"
        : R16(d) : "r"(a0), "r"(a1), "r"(a2), "r"(a3), "l"(b));
}
__device__ __forceinline__ void rs32_z(float* d, uint32_t a0, uint32_t a1, uint32_t a2, uint32_t a3, uint64_t b) {
    asm volatile("wgmma.mma_async.sync.aligned.m64n32k16.f32.bf16.bf16 " L16 ", {%16,%17,%18,%19}, %20, 0, 1, 1, 0;\n"
        : WO16(d) : "r"(a0), "r"(a1), "r"(a2), "r"(a3), "l"(b));
}
__device__ __forceinline__ void stsm_x4(uint32_t addr, uint32_t r0, uint32_t r1, uint32_t r2, uint32_t r3) {
    asm volatile("stmatrix.sync.aligned.m8n8.x4.shared.b16 [%0], {%1, %2, %3, %4};" :: "r"(addr), "r"(r0), "r"(r1), "r"(r2), "r"(r3) : "memory");
}
__device__ __forceinline__ uint32_t lds32(uint32_t a) { uint32_t v; asm volatile("ld.shared.u32 %0, [%1];" : "=r"(v) : "r"(a) : "memory"); return v; }
__device__ __forceinline__ uint2 lds64(uint32_t a) { uint2 v; asm volatile("ld.shared.v2.u32 {%0, %1}, [%2];" : "=r"(v.x), "=r"(v.y) : "r"(a) : "memory"); return v; }
__device__ __forceinline__ uint4 lds128(uint32_t a) { uint4 v; asm volatile("ld.shared.v4.u32 {%0, %1, %2, %3}, [%4];" : "=r"(v.x), "=r"(v.y), "=r"(v.z), "=r"(v.w) : "r"(a) : "memory"); return v; }
__device__ __forceinline__ void sts32(uint32_t a, uint32_t x) { asm volatile("st.shared.u32 [%0], %1;" :: "r"(a), "r"(x) : "memory"); }
__device__ __forceinline__ void sts128(uint32_t a, uint32_t x, uint32_t y, uint32_t z, uint32_t w) {
    asm volatile("st.shared.v4.u32 [%0], {%1, %2, %3, %4};" :: "r"(a), "r"(x), "r"(y), "r"(z), "r"(w) : "memory");
}
__device__ __forceinline__ float bflo(uint32_t v) { return __uint_as_float(v << 16); }
__device__ __forceinline__ float bfhi(uint32_t v) { return __uint_as_float(v & 0xffff0000u); }
__device__ __forceinline__ uint32_t hmul2bf(uint32_t a, uint32_t b) { uint32_t r; asm("mul.rn.bf16x2 %0, %1, %2;" : "=r"(r) : "r"(a), "r"(b)); return r; }
__device__ __forceinline__ void mbar_init(uint32_t a, uint32_t c) { asm volatile("mbarrier.init.shared.b64 [%0], %1;" :: "r"(a), "r"(c)); }
__device__ __forceinline__ void mbar_wait(uint32_t a, uint32_t ph) {
    asm volatile("{\n.reg .pred p;\n.reg .u32 n;\nmov.u32 n, 0;\nWAIT_LOOP:\nmbarrier.try_wait.parity.shared.b64 p, [%0], %1;\n@p bra DONE;\nadd.u32 n, n, 1;\nsetp.lt.u32 p, n, 4000000;\n@p bra WAIT_LOOP;\nDONE:\n}" :: "r"(a), "r"(ph) : "memory");
}
__device__ __forceinline__ void mbar_wait_n(uint32_t a, uint32_t ph, uint32_t& n) {
    asm volatile("{\n.reg .pred p;\nWAIT_LOOP:\nmbarrier.try_wait.parity.shared.b64 p, [%1], %2;\n@p bra DONE;\nadd.u32 %0, %0, 1;\nsetp.lt.u32 p, %0, 4000000;\n@p bra WAIT_LOOP;\nDONE:\n}" : "+r"(n) : "r"(a), "r"(ph) : "memory");
}
__device__ __forceinline__ void mbar_expect_tx(uint32_t a, uint32_t bytes) { asm volatile("mbarrier.arrive.expect_tx.shared.b64 _, [%0], %1;" :: "r"(a), "r"(bytes) : "memory"); }
__device__ __forceinline__ void mbar_arrive(uint32_t a) { asm volatile("mbarrier.arrive.shared.b64 _, [%0];" :: "r"(a) : "memory"); }
__device__ __forceinline__ void mbar_arrive2(uint32_t a) { asm volatile("mbarrier.arrive.shared.b64 _, [%0], 2;" :: "r"(a) : "memory"); }
__device__ __forceinline__ void tma_load_2d(uint32_t dst, const CUtensorMap* map, int c0, int c1, uint32_t bar) {
    asm volatile("cp.async.bulk.tensor.2d.shared::cluster.global.mbarrier::complete_tx::bytes [%0], [%1, {%3, %4}], [%2];"
        :: "r"(dst), "l"(map), "r"(bar), "r"(c0), "r"(c1) : "memory");
}
__device__ __forceinline__ void tma_load_3d(uint32_t dst, const CUtensorMap* map, int c0, int c1, int c2, uint32_t bar) {
    asm volatile("cp.async.bulk.tensor.3d.shared::cluster.global.mbarrier::complete_tx::bytes [%0], [%1, {%3, %4, %5}], [%2];"
        :: "r"(dst), "l"(map), "r"(bar), "r"(c0), "r"(c1), "r"(c2) : "memory");
}
__device__ __forceinline__ void tma_load_4d(uint32_t dst, const CUtensorMap* map, int c0, int c3, uint32_t bar) {
    asm volatile("cp.async.bulk.tensor.4d.shared::cluster.global.mbarrier::complete_tx::bytes [%0], [%1, {%3, %5, %5, %4}], [%2];"
        :: "r"(dst), "l"(map), "r"(bar), "r"(c0), "r"(c3), "r"(0) : "memory");
}
__device__ __forceinline__ void tma_load_5d(uint32_t dst, const CUtensorMap* map, int c0, int c4, uint32_t bar) {
    asm volatile("cp.async.bulk.tensor.5d.shared::cluster.global.mbarrier::complete_tx::bytes [%0], [%1, {%3, %5, %5, %5, %4}], [%2];"
        :: "r"(dst), "l"(map), "r"(bar), "r"(c0), "r"(c4), "r"(0) : "memory");
}
__device__ __forceinline__ void bulk_load(uint32_t dst, const void* src, uint32_t bytes, uint32_t bar) {
    asm volatile("cp.async.bulk.shared::cluster.global.mbarrier::complete_tx::bytes [%0], [%1], %2, [%3];" :: "r"(dst), "l"(src), "r"(bytes), "r"(bar) : "memory");
}
__device__ __forceinline__ void wait_counter(const unsigned int* p, unsigned int target) {
    unsigned int cur; int spins = 0;
    #pragma unroll 1
    do {
        asm volatile("ld.relaxed.gpu.global.u32 %0, [%1];" : "=r"(cur) : "l"(p) : "memory");
        if ((int)(cur - target) >= 0) break;
        __nanosleep(20);
    } while (++spins < (1 << 22));
}
__device__ __forceinline__ void red_release(unsigned int* p) { asm volatile("red.release.gpu.global.add.u32 [%0], 1;" :: "l"(p) : "memory"); }
__device__ __forceinline__ uint32_t clk32() { uint32_t c; asm volatile("mov.u32 %0, %%clock;" : "=r"(c)); return c; }
__device__ __forceinline__ bool elect_one() {
    uint32_t r;
    asm volatile("{\n.reg .pred p;\nelect.sync _|p, 0xffffffff;\nselp.u32 %0, 1, 0, p;\n}" : "=r"(r));
    return r != 0;
}
__device__ __forceinline__ int tid128() { int t; asm volatile("mov.u32 %0, %%tid.x;" : "=r"(t)); return t & 127; }
typedef __nv_bfloat162 bf2;
__device__ __forceinline__ bf2 asbf2(uint32_t v) { return *reinterpret_cast<bf2*>(&v); }
__device__ __forceinline__ uint32_t asu32(bf2 v) { return *reinterpret_cast<uint32_t*>(&v); }
template <int M> struct W16 { static constexpr uint32_t c = ct::bf16bits(ct::cos2048(128 * M)) * 0x10001u, s = ct::bf16bits(-ct::sin2048(128 * M)) * 0x10001u; };
__device__ __forceinline__ void pin(bf2& v) { uint32_t u = asu32(v); asm volatile("" : "+r"(u) :: "memory"); v = asbf2(u); }
__device__ __forceinline__ bf2 neg2(bf2 v) { return asbf2(asu32(v) ^ 0x80008000u); }
__device__ __forceinline__ void cmul2(bf2& r, bf2& i, bf2 wr, bf2 wi) {
    const bf2 a = r, b = i;
    r = __hfma2(a, wr, __hmul2(b, neg2(wi))); i = __hfma2(b, wr, __hmul2(a, wi));
}
__device__ __forceinline__ void bfly4(bf2* r, bf2* i, int o, int s) {
    const bf2 ar = __hadd2(r[o], r[o + 2 * s]), ai = __hadd2(i[o], i[o + 2 * s]), br = __hsub2(r[o], r[o + 2 * s]), bi = __hsub2(i[o], i[o + 2 * s]);
    const bf2 cr = __hadd2(r[o + s], r[o + 3 * s]), ci = __hadd2(i[o + s], i[o + 3 * s]), dr = __hsub2(r[o + s], r[o + 3 * s]), di = __hsub2(i[o + s], i[o + 3 * s]);
    r[o] = __hadd2(ar, cr); i[o] = __hadd2(ai, ci); r[o + 2 * s] = __hsub2(ar, cr); i[o + 2 * s] = __hsub2(ai, ci);
    r[o + s] = __hadd2(br, di); i[o + s] = __hsub2(bi, dr); r[o + 3 * s] = __hsub2(br, di); i[o + 3 * s] = __hadd2(bi, dr);
}
template <int M> __device__ __forceinline__ void tw16(bf2& r, bf2& i) {
    if (M == 4) { const bf2 a = r; r = i; i = neg2(a); }
    else cmul2(r, i, asbf2(W16<M>::c), asbf2(W16<M>::s));
}
__device__ __forceinline__ void tw16_all(bf2* r, bf2* i) {
    tw16<1>(r[5], i[5]); tw16<2>(r[6], i[6]); tw16<3>(r[7], i[7]); tw16<2>(r[9], i[9]); tw16<4>(r[10], i[10]); tw16<6>(r[11], i[11]);
    tw16<3>(r[13], i[13]); tw16<6>(r[14], i[14]); tw16<9>(r[15], i[15]);
}

__device__ __forceinline__ void dft16(bf2* r, bf2* i) {
    #pragma unroll
    for (int r0 = 0; r0 < 4; r0++) bfly4(r, i, r0, 4);
    tw16_all(r, i);
    #pragma unroll
    for (int k1 = 0; k1 < 4; k1++) bfly4(r, i, 4 * k1, 1);
}
__device__ __forceinline__ void idft16(bf2* r, bf2* i) {
    #pragma unroll
    for (int k1 = 0; k1 < 4; k1++) bfly4(i, r, 4 * k1, 1);
    tw16_all(i, r);
    #pragma unroll
    for (int r0 = 0; r0 < 4; r0++) bfly4(i, r, r0, 4);
}

#define DBAR 1
#define FBAR 2
#define TBAR 4
#define HBAR 6
#define GBAR 10
#define LBAR 11
#define FULL(s) (bars + 8 * (s))
#define EMPTY(s) (bars + 8 * (RING + (s)))
#define XB (bars + 64)
#define X1B(h) (bars + 72 + 8 * (h))
#define ZOK (bars + 88)
#define EPB (bars + 96)
#define R0F (bars + 104)
#define HOK(i) (bars + 112 + 8 * (i))
#define WQ(i) (bars + 144 + 8 * (i))
#define EPO_OFF (BAR_OFF + 176)
#define ROLE_OFF (BAR_OFF + 180)
#define SACT_OFF (BAR_OFF + 184)
#define PT_OFF (R2 + 26624)
#define LAM_OFF (R2 + 27648)
#define WBUF(i) ((i) == 1 ? R1 : ((i) == 2 ? R1 + 16384 : R2 + 10240))
#define PC1 448
#define PC1M 256
#define P1END 8500
#define PC2 88
#define PCR 96
#define PCH 160
#define PCL 100
#define PCW 200
#define PCZ 500
#define NZ 4
#define TXT 1400
#define TTAB 8500
#define PFW 5000
#define PFB 9000
#define PFC 12000
#define PFCS 2000
__device__ __forceinline__ void delay(int cycles) { const uint32_t c = clk32(); while ((int)(clk32() - c) < cycles) { } }
__device__ __forceinline__ void pace(uint32_t& t, int cycles) { while ((int)(clk32() - t) < 0) { } t += cycles; }
__device__ __forceinline__ void pf_line(const void* p) { asm volatile("prefetch.global.L2 [%0];" :: "l"(p)); }

__device__ __forceinline__ float2 cis(int m) { return __ldg(reinterpret_cast<const float2*>(g_img.cs[m & 15][(m >> 4) & 127])); }
__device__ __forceinline__ void gen_dft(uint32_t dst, int j, float2 w, float2 b, int b0, int b1, float c0) {
    const float c2 = 2.f * w.x;
    float2 a = cmul(b, w);
    float2 z0 = b0 ? b : make_float2(c0, (j & 1) ? -c0 : c0);
    dst += j * 128;
    #pragma unroll 1
    for (int blk = b0; blk < b1; blk++) {
        float2 v[9];
        v[0] = b;
        v[1] = make_float2(fmaf(c2, b.x, -a.x), fmaf(c2, b.y, -a.y));
        #pragma unroll
        for (int k = 2; k < 9; k++) v[k] = make_float2(fmaf(c2, v[k - 1].x, -v[k - 2].x), fmaf(c2, v[k - 1].y, -v[k - 2].y));
        const uint32_t p = dst + (blk >> 2) * 16384, c = (2 * (blk & 3)) ^ (j & 7);
        sts128(p + c * 16, pack2(z0.x, v[1].x), pack2(v[2].x, v[3].x), pack2(v[4].x, v[5].x), pack2(v[6].x, v[7].x));
        sts128(p + (c ^ 1) * 16, pack2(z0.y, v[1].y), pack2(v[2].y, v[3].y), pack2(v[4].y, v[5].y), pack2(v[6].y, v[7].y));
        a = v[7]; b = v[8]; z0 = b;
    }
}

__device__ __forceinline__ void fft_p1(uint32_t sbase, uint32_t bars, int tile, int r, int db, uint32_t t_end) {
    constexpr uint32_t s16 = SBASE / 16;
    float acc[64];
    wgmma_fence();
    ss128_z<1, 1>(acc, mkd(s16 + tile * 1024, R1, 16384, 1024, 1), mkd(s16, R0, 16384, 1024, 1));
    #pragma unroll
    for (int ks = 1; ks < 8; ks++) ss128<1, 1>(acc, mkd(s16 + tile * 1024, R1 + ks * 2048, 16384, 1024, 1), mkd(s16, R0 + ks * 2048, 16384, 1024, 1));
    wgmma_commit();
    const int tid = tid128();
    float g0 = 0.f;
    uint4* dst = g_X1 + (64 * tile + 2 * (tid >> 2)) * 2048 + (r >> 3) * 1024 + db * 128 + (r & 7) * 16 + (tid & 3);
    wgmma_wait<0>();
    reg_fence<64>(acc);
    uint32_t tp = clk32();
    const int dt = min(max((int)(t_end - tp) >> 3, PC1M), PC1);
    tp += (threadIdx.x >> 5 & 7) * (dt >> 3);
    #pragma unroll
    for (int c = 0; c < 4; c++) {
        const float* u = acc + 4 * (c >> 1) + (c & 1);
        #pragma unroll
        for (int ke = 0; ke < 2; ke++) {
            float v[8];
            #pragma unroll
            for (int z = 0; z < 8; z++) { const int ix = 8 * (z & 3) + 2 * (z >> 2); v[z] = ke ? u[ix] - u[ix + 32] : u[ix] + u[ix + 32]; }
            uint4 o = make_uint4(pack2(v[0], v[1]), pack2(v[2], v[3]), pack2(v[4], v[5]), pack2(v[6], v[7]));
            asm volatile("" : "+r"(o.x), "+r"(o.y), "+r"(o.z), "+r"(o.w) :: "memory");
            pace(tp, dt);
            __stcg(dst + ke * 2048 + 4 * c, o);
            if (c < 2) {
                #pragma unroll
                for (int k = 4 * c + 2 * ke; k < 4 * c + 2 * ke + 2; k++) {
                    const uint4 x = lds128(sbase + R0 + tile * 16384 + tid * 128 + ((k ^ (tid & 7)) << 4)), gv = lds128(sbase + GATE_OFF + tile * 128 + k * 16);
                    const uint32_t p0 = hmul2bf(x.x, gv.x), p1 = hmul2bf(x.y, gv.y), p2 = hmul2bf(x.z, gv.z), p3 = hmul2bf(x.w, gv.w);
                    g0 += ((bflo(p0) + bfhi(p0)) + (bflo(p1) + bfhi(p1))) + ((bflo(p2) + bfhi(p2)) + (bflo(p3) + bfhi(p3)));
                }
            }
            if (c == 1 && ke == 1) {
                __stcg(&g_gp[(16 * r + 2 * db + tile) * 128 + tid], g0);
                __syncwarp();
                if ((tid & 31) == 0) mbar_arrive(R0F);
            }
        }
    }
}

__device__ __forceinline__ int w_first(int unit, int hb) { const int ka = unit >> 1, ke = unit & 1; return hb ? ((128 - ka) & 127) * 513 + 2 - ke : ka * 513 + ke; }
__device__ __forceinline__ void load_w(const CUtensorMap* wm, uint32_t sbase, int unit, int i) {
    const uint32_t bars = sbase + BAR_OFF;
    mbar_expect_tx(WQ(i), 16384);
    #pragma unroll 1
    for (int a = 0; a < 4; a++) { tma_load_3d(sbase + WBUF(i) + a * 4096, wm + (i & 1), w_first(unit, i >> 1) & ~15, 0, 4 * a, WQ(i)); delay(PCW); }
}
__device__ __forceinline__ uint32_t w_off(int e) { e &= 511; return (e >> 6) * 128 + ((((e >> 3) ^ (e >> 6)) & 7) << 4) + (e & 7) * 2; }
__device__ __forceinline__ void sts16(uint32_t a, uint32_t v) { asm volatile("st.shared.u16 [%0], %1;" :: "r"(a), "h"((unsigned short)v) : "memory"); }
__device__ __forceinline__ void boundary() { while (clk32() == 0) { } asm volatile("" ::: "memory"); }
__device__ __forceinline__ void yield_to_scan(uint32_t sbase) {
    #pragma unroll 1
    for (int n = 0; n < 100000 && lds32(sbase + SACT_OFF); n++) __nanosleep(50);
}
template <int OFF> __device__ __forceinline__ uint32_t lds_w(uint32_t a, uint32_t b) {
    uint32_t l, h;
    asm volatile("ld.shared.u16 %0, [%2 + %4];\nld.shared.u16 %1, [%3 + %4];" : "=r"(l), "=r"(h) : "r"(a), "r"(b), "n"(OFF) : "memory");
    return __byte_perm(l, h, 0x5410);
}
template <int S> __device__ __forceinline__ void load_ws(uint32_t* w, uint32_t a, uint32_t b) {
    if constexpr (S < 16) { w[S] = lds_w<((S >> 2) + 4 * (S & 3)) * 1024>(a, b); load_ws<S + 1>(w, a, b); }
}
template <int I> __device__ __forceinline__ void fetch_w(uint32_t* w, uint32_t sbase, int unit) {
    constexpr int hb = I >> 1;
    const uint32_t bars = sbase + BAR_OFF, buf = sbase + WBUF(I);
    const int tid = tid128(), sh = w_first(unit, hb) & 15;
    const uint32_t pt = lds32(sbase + PT_OFF + 512 * hb + 4 * tid) >> (16 * (I & 1)), sp = lds32(sbase + DSK_OFF + 4 * (tid & 31)) >> (16 * (I & 1));
    mbar_wait(WQ(I), 0);
    if ((sh & 1) + 2 * (tid & 7) + 2 <= sh) sts16(buf + (tid >> 3) * 1024 + ((sh & 1) + 2 * (tid & 7)) * 2, pt);
    bar_sync_n(FBAR, 128);
    if (!(unit & 1) && (tid >> 4) == hb) sts16(buf + w_off(sh + 510 * hb) + (tid & 15) * 1024, sp);
    __syncwarp();
    boundary();
    const int pos = 128 * (tid & 3) + 2 * (tid >> 2);
    const bool rot = hb && unit >= 2;
    const uint32_t o0 = buf + w_off(sh + (hb ? 510 - pos : pos)) - (rot ? 1024 : 0), o1 = buf + w_off(sh + (hb ? 446 - pos : pos + 64)) - (rot ? 1024 : 0), oz = rot ? 16384 : 0;
    w[0] = lds_w<0>(o0 + oz, o1 + oz);
    load_ws<1>(w, o0, o1);
}
__device__ __forceinline__ void pin16(bf2* r, bf2* i) {
    #pragma unroll
    for (int k = 0; k < 16; k++) { pin(r[k]); pin(i[k]); }
}

__device__ __forceinline__ void fft_p2(uint32_t sbase, uint32_t bars, int unit, const __nv_bfloat16* w_r, const __nv_bfloat16* w_i) {
    constexpr uint32_t s16 = SBASE / 16;
    const ct::Half* tb = &g_img.h[unit & 1];
    uint32_t P[16][4];
    uint32_t wr[16], wi[16];
    {
        const int tid = tid128();
        uint32_t sp = 0, pt[2] = {0, 0};
        const uint4 t = __ldg(reinterpret_cast<const uint4*>(tb->tw[0][tid]));
        if (tid < 32 && !(unit & 1)) {
            const int k1 = ((tid & 16) ? (128 - (unit >> 1)) & 127 : unit >> 1) + 128 * (tid & 15), o1 = k1 * 513 + 32 * (tid & 16), o2 = ((2048 - k1) & 2047) * 513 + 32 * (tid & 16);
            sp = pack2(0.5f * (__bfloat162float(w_r[o1]) + __bfloat162float(w_r[o2])), 0.5f * (__bfloat162float(w_i[o1]) - __bfloat162float(w_i[o2])));
        }
        #pragma unroll
        for (int hb = 0; hb < 2; hb++) {
            const int e0 = w_first(unit, hb), z = (e0 & 1) + 2 * (tid & 7), o = (tid >> 3) * 65664 + (e0 & ~15) + 512 + z;
            if (z + 2 <= (e0 & 15)) pt[hb] = reinterpret_cast<const unsigned short*>(w_r)[o] | ((uint32_t)reinterpret_cast<const unsigned short*>(w_i)[o] << 16);
        }
        sts32(sbase + PT_OFF + 4 * tid, pt[0]); sts32(sbase + PT_OFF + 512 + 4 * tid, pt[1]);
        mbar_wait(X1B(0), 0);
        if (tid < 32) sts32(sbase + DSK_OFF + 4 * tid, sp);
        if (unit >= 128) {
            mbar_wait(X1B(1), 0);
            #pragma unroll 1
            for (int i = 0; i < 16; i++) {
                const float2 w = cis(-64 * ((i & 8) + (tid >> 4)));
                const uint32_t a = sbase + R1 + (i * 128 + tid) * 16;
                const uint2 v = lds64(a + 8);
                sts128(a, pack2(bflo(v.x) * w.x, bfhi(v.x) * w.x), pack2(bflo(v.y) * w.x, bfhi(v.y) * w.x), pack2(bflo(v.x) * w.y, bfhi(v.x) * w.y), pack2(bflo(v.y) * w.y, bfhi(v.y) * w.y));
            }
            fence_async();
            bar_sync_n(FBAR, 128);
        }
        #pragma unroll
        for (int h = 0; h < 2; h++) {
            float acc[64];
            if (h) mbar_wait(X1B(1), 0);
            wgmma_fence();
            ss128_z<1, 0>(acc, mkd(s16, R2, 1024, 128), mkd(s16, R1 + h * 16384, 2048, 128));
            #pragma unroll
            for (int s = 1; s < 4; s++) ss128<1, 0>(acc, mkd(s16, R2 + s * 2048, 1024, 128), mkd(s16, R1 + h * 16384 + s * 4096, 2048, 128));
            wgmma_commit();
            if (h == 1) {
                fetch_w<0>(wr, sbase, unit);
                #pragma unroll
                for (int s = 0; s < 16; s++) asm volatile("" : "+r"(wr[s]) :: "memory");
                if (unit > 999) sts32(sbase + SACT_OFF + 4, wr[15]);
            }
            wgmma_wait<0>();
            reg_fence<64>(acc);
            bar_arrive_n(LBAR + h, 160);
            bf2 f[32];
            #pragma unroll
            for (int z = 0; z < 32; z++) { uint32_t u = pack2(acc[2 * z], acc[2 * z + 1]); asm volatile("" : "+r"(u) :: "memory"); f[z] = asbf2(u); }
            boundary();
            float d[2][16];
            #pragma unroll
            for (int pr = 0; pr < 5; pr++) {
                if (pr == 2) boundary();
                if (pr < 4) {
                    bf2* a = f + 8 * pr;
                    #pragma unroll
                    for (int z = 0; z < 8; z++) pin(a[z]);
                    #pragma unroll
                    for (int z = 0; z < 4; z++) cmul2(a[2 * z], a[2 * z + 1], asbf2((z & 1) ? t.z : t.x), asbf2((z & 1) ? t.w : t.y));
                    wgmma_fence();
                    rs32_z(d[pr & 1], asu32(a[0]), asu32(a[4]), asu32(a[2]), asu32(a[6]), mkd(s16, B16F_OFF, 128, 512));
                    rs32(d[pr & 1], asu32(a[1]), asu32(a[5]), asu32(a[3]), asu32(a[7]), mkd(s16, B16F_OFF + 256, 128, 512));
                    wgmma_commit();
                }
                if (pr > 0) {
                    if (pr < 4) wgmma_wait<1>(); else wgmma_wait<0>();
                    reg_fence<16>(d[(pr - 1) & 1]);
                    #pragma unroll
                    for (int z = 0; z < 8; z++) {
                        uint32_t& p = P[8 * h + 2 * pr - 2 + (z & 1)][z >> 1];
                        p = pack2(d[(pr - 1) & 1][2 * z], d[(pr - 1) & 1][2 * z + 1]);
                        asm volatile("" : "+r"(p) :: "memory");
                    }
                }
            }
        }
    }
    {
        bf2 vr[2][16], vi[2][16];
        #pragma unroll
        for (int r = 0; r < 16; r++) { vr[0][r] = asbf2(P[r][0]); vr[1][r] = asbf2(P[r][1]); vi[0][r] = asbf2(P[r][2]); vi[1][r] = asbf2(P[r][3]); }
        fetch_w<1>(wi, sbase, unit);
        pin16(vr[0], vi[0]);
        dft16(vr[0], vi[0]);
        #pragma unroll
        for (int s = 0; s < 16; s++) cmul2(vr[0][s], vi[0][s], asbf2(wr[s]), asbf2(wi[s]));
        fetch_w<2>(wr, sbase, unit);
        pin16(vr[1], vi[1]);
        dft16(vr[1], vi[1]);
        fetch_w<3>(wi, sbase, unit);
        pin16(vr[0], vi[0]);
        idft16(vr[0], vi[0]);
        #pragma unroll
        for (int s = 0; s < 16; s++) cmul2(vr[1][s], vi[1][s], asbf2(wr[s]), asbf2(wi[s]));
        bar_sync_n(FBAR, 128);
        idft16(vr[1], vi[1]);
        #pragma unroll
        for (int r = 0; r < 16; r++) { P[r][0] = asu32(vr[0][r]); P[r][1] = asu32(vr[1][r]); P[r][2] = asu32(vi[0][r]); P[r][3] = asu32(vi[1][r]); }
    }
    {
        const int tid = tid128(), ka = unit >> 1;
        const uint4 t = __ldg(reinterpret_cast<const uint4*>(tb->tw[1][tid]));
        const uint32_t zero = unit >> 8;
        const uint32_t sa = sbase + R1 + ((tid >> 3) & 1) * 1024 + (2 * (tid >> 5) + ((tid >> 4) & 1)) * 128 + (tid & 7) * 16;
        uint8_t* dst = reinterpret_cast<uint8_t*>(g_X2) + (2 * (tid >> 5)) * X2_IMG + (unit & 1) * (X2_IMG / 2)
                     + (16 * (ka >> 3) + 8 * ((tid >> 4) & 1) + (ka & 7)) * 128 + ((((tid >> 1) & 7) ^ (ka & 7)) << 4) + (tid & 1) * 8;
        uint32_t o[32];
        #pragma unroll
        for (int h = 0; h < 2; h++) {
            float d[2][16];
            #pragma unroll
            for (int pr = 0; pr < 5; pr++) {
                if (!(pr & 1)) { if (h) yield_to_scan(sbase); else boundary(); }
                if (pr < 4) {
                    uint32_t a[8];
                    #pragma unroll
                    for (int z = 0; z < 8; z++) asm volatile("xor.b32 %0, %1, %2;" : "=r"(a[z]) : "r"(P[8 * h + 2 * pr + (z >> 2)][z & 3]), "r"(zero) : "memory");
                    wgmma_fence();
                    rs32_z(d[pr & 1], a[0], a[4], a[1], a[5], mkd(s16, R2 + 8192, 128, 512));
                    rs32(d[pr & 1], a[2], a[6], a[3], a[7], mkd(s16, R2 + 8192 + 256, 128, 512));
                    wgmma_commit();
                }
                if (h) {
                    #pragma unroll
                    for (int z = 2 * pr; z < 2 * pr + 2; z++) __stcg(reinterpret_cast<uint2*>(dst + (8 * (z >> 1) + (z & 1)) * X2_IMG), make_uint2(o[2 * z], o[2 * z + 1]));
                }
                if (pr > 0) {
                    if (pr < 4) wgmma_wait<1>(); else wgmma_wait<0>();
                    reg_fence<16>(d[(pr - 1) & 1]);
                    #pragma unroll
                    for (int rl = 0; rl < 2; rl++) {
                        const float* a = d[(pr - 1) & 1] + 2 * rl;
                        bf2 r0 = asbf2(pack2(a[0], a[1])), r1 = asbf2(pack2(a[4], a[5])), i0 = asbf2(pack2(a[8], a[9])), i1 = asbf2(pack2(a[12], a[13]));
                        cmul2(r0, i0, asbf2(t.x), asbf2(t.y)); cmul2(r1, i1, asbf2(t.z), asbf2(t.w));
                        stsm_x4(sa + (8 * h + 2 * pr - 2 + rl) * 2048, asu32(r0), asu32(r1), asu32(i0), asu32(i1));
                    }
                }
            }
            fence_async();
            bar_sync_n(FBAR, 128);
            boundary();
            float acc[64];
            wgmma_fence();
            ss128_z<0, 1>(acc, mkd(s16, R2, 128, 1024), mkd(s16, R1 + h * 16384, 128, 1024));
            #pragma unroll
            for (int s = 1; s < 4; s++) ss128<0, 1>(acc, mkd(s16, R2 + s * 256, 128, 1024), mkd(s16, R1 + h * 16384 + s * 256, 128, 1024));
            wgmma_commit();
            uint32_t tp = clk32();
            if (h) {
                #pragma unroll
                for (int z = 10; z < 16; z++) { if (!(z & 1)) pace(tp, 2 * PC2); __stcg(reinterpret_cast<uint2*>(dst + (8 * (z >> 1) + (z & 1)) * X2_IMG), make_uint2(o[2 * z], o[2 * z + 1])); }
            }
            wgmma_wait<0>();
            reg_fence<64>(acc);
            #pragma unroll
            for (int z = 0; z < 16; z++) { const float* a = acc + 8 * (z >> 1) + 2 * (z & 1); o[2 * z] = pack2(a[0], a[1]); o[2 * z + 1] = pack2(a[4], a[5]); asm volatile("" : "+r"(o[2 * z]), "+r"(o[2 * z + 1]) :: "memory"); }
            if (h) {
                yield_to_scan(sbase);
                tp = clk32() + (tid >> 5) * (PC2 / 2);
                #pragma unroll
                for (int z = 0; z < 16; z++) { if (!(z & 1)) pace(tp, 2 * PC2); __stcg(reinterpret_cast<uint2*>(dst + (64 + 8 * (z >> 1) + (z & 1)) * X2_IMG), make_uint2(o[2 * z], o[2 * z + 1])); }
            }
        }
    }
}

struct Maps { CUtensorMap BB, X, Xr, Cre, Cim, W[2]; };

template <int S> __device__ __forceinline__ void release(uint32_t rel, uint32_t bars) {
    mbar_arrive(EMPTY(S));
    asm volatile("mbarrier.arrive.shared::cluster.b64 _, [%0 + %1];" :: "r"(rel), "n"(8 * (RING + S)) : "memory");
}
__device__ __forceinline__ int peer_role(uint32_t a) { int v; asm volatile("ld.shared::cluster.u32 %0, [%1];" : "=r"(v) : "r"(a ^ (1u << 24)) : "memory"); return v; }
__device__ __forceinline__ void tma_load_3d_mc(uint32_t dst, const CUtensorMap* map, int c0, int c1, int c2, uint32_t bar) {
    asm volatile("cp.async.bulk.tensor.3d.shared::cluster.global.mbarrier::complete_tx::bytes.multicast::cluster [%0], [%1, {%3, %4, %5}], [%2], %6;"
        :: "r"(dst), "l"(map), "r"(bar), "r"(c0), "r"(c1), "r"(c2), "h"((unsigned short)3) : "memory");
}
__device__ __forceinline__ void bulk_load_mc(uint32_t dst, const void* src, uint32_t bytes, uint32_t bar) {
    asm volatile("cp.async.bulk.shared::cluster.global.mbarrier::complete_tx::bytes.multicast::cluster [%0], [%1], %2, [%3], %4;"
        :: "r"(dst), "l"(src), "r"(bytes), "r"(bar), "h"((unsigned short)3) : "memory");
}
template <int TA> __device__ __forceinline__ void mma_round(float* acc, uint32_t bars, uint32_t a16, uint32_t ph, bool lead, int accum, int it, uint32_t& nw, uint32_t peer, int pp, bool lag = false) {
    #pragma unroll
    for (int s = 0; s < RING; s++) {
        if (TA && (s == 1 || s == 2) && lag) bar_sync_n(TBAR + s - 1, 256);
        mbar_wait_n(FULL(s), ph, nw);
        if (!TA || accum < 7 || (s == 0 && !lag)) bar_sync_n(pp, 256);
        wgmma_fence();
        #pragma unroll
        for (int k = 0; k < 4; k++) {
            const uint64_t da = TA ? mkd(a16, s * STGB + k * 256, 128, 1024) : mkd(a16, s * STGB + k * 32, 16, 1024, 1);
            const uint64_t db = mkd(SBASE / 16, s * STGB + 16384 + k * 32, 16, 1024, 1);
            if (k == 0 && s == 0) ss128_p<TA, 0>(acc, da, db, accum); else ss128<TA, 0>(acc, da, db);
        }
        wgmma_commit();
        if (!TA || accum < 7) bar_arrive_n(14 - pp, 256);
        wgmma_wait<1>();
        if (lead && (s > 0 ? (!TA || accum < 7) : accum != 0)) { if (s == 0) release<3>(peer, bars); if (s == 1) release<0>(peer, bars); if (s == 2) release<1>(peer, bars); if (s == 3) release<2>(peer, bars); }
    }
}
__device__ __forceinline__ void gemm_main(float* A, uint32_t sbase, int wg, int warp, int lane, int cb, int tc, int swp) {
    const uint32_t bars = sbase + BAR_OFF;
    const bool lead = tid128() == 0;
    const uint32_t a16 = SBASE / 16 + wg * 512;
    uint32_t nw = 0;
    uint32_t peer = bars ^ ((uint32_t)(lane + 1) << 24);
    asm volatile("" : "+r"(peer));
    asm volatile("barrier.cluster.wait.acquire.aligned;" ::: "memory");
    if (wg) bar_arrive_n(0, 256);
    uint32_t a = sbase + R0 + (((lane >> 3) & 1) ^ swp) * 16384 + (lane >> 4) * 1024 + (wg * 32 + warp * 8 + (lane & 7)) * 16;
    uint32_t pa = sbase + LAM_OFF + (wg * 32 + warp * 8 + (lane >> 2)) * 16;
    unsigned long long* ag = &g_agg[tc * P_DIM + cb * 128 + wg * 32 + warp * 8 + (lane >> 2)];
    asm volatile("" : "+r"(a), "+r"(pa), "+l"(ag));
    #pragma unroll 1
    for (int half = 0; half < 2; half++) {
        uint2 p0;
        uint4 p1;
        uint32_t par;
        #pragma unroll 1
        for (int rd = 0; rd < 4; rd++) {
            if (rd == 3) { mbar_wait_n(EPB, 0, nw); p0 = lds64(pa); p1 = lds128(pa + 2048); par = lds32(sbase + EPO_OFF); }
            mma_round<0>(A, bars, a16, rd & 1, lead, rd, 16 * half + 4 * rd, nw, peer, 14 * wg);
        }
        mbar_wait_n(R0F, half, nw);
        const float2 lam = make_float2(__uint_as_float(p0.x), __uint_as_float(p0.y));
        const float2 l16 = make_float2(__uint_as_float(p1.x), __uint_as_float(p1.y)), l32 = make_float2(__uint_as_float(p1.z), __uint_as_float(p1.w)), l64 = cmul(l32, l32);
        wgmma_wait<0>();
        reg_fence<64>(A);
        if (lead) release<RING - 1>(peer, bars);
        #pragma unroll
        for (int r = 1; r < 16; r++) {
            #pragma unroll
            for (int c = 0; c < 2; c++) {
                const float2 v = cfma(lam, make_float2(A[4 * r - 4 + c], A[4 * r - 2 + c]), make_float2(A[4 * r + c], A[4 * r + 2 + c]));
                A[4 * r + c] = v.x; A[4 * r + 2 + c] = v.y;
            }
            if ((r & 1) && r < 12) { const float* u = A + 4 * r - 4; stsm_x4(a + (r >> 1) * 2048, pack2(u[0], u[1]), pack2(u[2], u[3]), pack2(u[4], u[5]), pack2(u[6], u[7])); }
        }
        {
            float2 e = cfma(l16, make_float2(A[60], A[62]), make_float2(A[61], A[63]));
            float2 o = make_float2(__shfl_xor_sync(0xffffffffu, e.x, 1), __shfl_xor_sync(0xffffffffu, e.y, 1));
            stsm_x4(a + 6 * 2048, pack2(A[48], A[49]), pack2(A[50], A[51]), pack2(A[52], A[53]), pack2(A[54], A[55]));
            e = cfma(l32, o, e);
            o = make_float2(__shfl_xor_sync(0xffffffffu, e.x, 2), __shfl_xor_sync(0xffffffffu, e.y, 2));
            stsm_x4(a + 7 * 2048, pack2(A[56], A[57]), pack2(A[58], A[59]), pack2(A[60], A[61]), pack2(A[62], A[63]));
            e = cfma(l64, o, e);
            if ((lane & 3) == 3)
                asm volatile("st.relaxed.gpu.global.v2.u32 [%0], {%1, %2};" :: "l"(ag),
                             "r"((__float_as_uint(swp ? e.y : e.x) & ~1u) | (par & 1u)), "r"((__float_as_uint(swp ? e.x : e.y) & ~1u) | (par & 1u)) : "memory");
        }
        pa += 1024; ag += 64;
        bar_arrive_n(DBAR, 384);
    }
    #pragma unroll 1
    for (int rd = 0; rd < 8; rd++) mma_round<1>(A, bars, a16, rd & 1, lead, rd, 32 + 4 * rd, nw, peer, 14 * wg, rd * wg == 7);
}

__device__ __forceinline__ const CUtensorMap* keep(const CUtensorMap* p) { return reinterpret_cast<const CUtensorMap*>(__shfl_sync(0xffffffffu, reinterpret_cast<unsigned long long>(p), 0)); }
__device__ __forceinline__ void produce(const Maps& mp, uint32_t sbase, int RK, int cb, int tc, int db, int rc) {
    const uint32_t bars = sbase + BAR_OFF;
    const CUtensorMap *mb = keep(&mp.BB), *mx = keep(&mp.X), *cr = keep(&mp.Cre), *ci = keep(&mp.Cim);
    if (!elect_one()) return;
    uint32_t nw = 0;
    int kc = 256, row = cb * 16;
    const int xj = tc * 8, xr = RK * 8;
    #pragma unroll 1
    for (int rd = 1; rd < 8; rd++) {
        #pragma unroll
        for (int s = 0; s < RING; s++) {
            mbar_wait_n(EMPTY(s), (rd - 1) & 1, nw);
            mbar_expect_tx(FULL(s), STGB);
            tma_load_3d_mc(sbase + s * STGB + 16384 + RK * 8192, mx, kc, xj, xr, FULL(s));
            tma_load_4d(sbase + s * STGB, mb, kc, row, FULL(s));
            asm volatile("add.s32 %0, %0, 64;" : "+r"(kc));
        }
        if (rd == 3) { kc = 0; row += 8; }
    }
    const uint8_t* hs = reinterpret_cast<const uint8_t*>(g_h) + rc * 32 * 16384 + RK * 8192;
    const int d0 = db * 4, d1 = db * 4 + 32;
    #pragma unroll 1
    for (int rd = 8; rd < 16; rd++) {
        const CUtensorMap* cm = (rd & 2) ? ci : cr;
        kc = (rd & 1) * 512 + (rd & 4) * 16;
        #pragma unroll
        for (int s = 0; s < RING; s++) {
            mbar_wait_n(EMPTY(s), (rd - 1) & 1, nw);
            mbar_expect_tx(FULL(s), STGB);
            if (s) bulk_load_mc(sbase + s * STGB + RK * 8192, hs, 8192, FULL(s));
            tma_load_5d(sbase + s * STGB + 16384, cm, kc, d0, FULL(s));
            tma_load_5d(sbase + s * STGB + 24576, cm, kc, d1, FULL(s));
            if (s == 0) { mbar_wait_n(HOK((rd >> 1) & 3), 0, nw); }
            if (!s) bulk_load_mc(sbase + s * STGB + RK * 8192, hs, 8192, FULL(s));
            asm volatile("add.s32 %0, %0, 128;" : "+r"(kc));
            asm volatile("add.s64 %0, %0, 16384;" : "+l"(hs));
        }
    }
    sts32(sbase + SACT_OFF + 4, 1u);
}

template <bool full> __global__ void __cluster_dims__(2, 1, 1) __launch_bounds__(640, 1)
fused_kernel(const __nv_bfloat16* __restrict__ x, const __nv_bfloat16* __restrict__ Bre, const __nv_bfloat16* __restrict__ Bim, int swp,
             const __nv_bfloat16* __restrict__ w_r, const __nv_bfloat16* __restrict__ w_i,
             const __nv_bfloat16* __restrict__ lam_re, const __nv_bfloat16* __restrict__ lam_im,
             const __nv_bfloat16* __restrict__ log_dt, const __nv_bfloat16* __restrict__ dskip,
             const __nv_bfloat16* __restrict__ gate_w,
             const __nv_bfloat16* __restrict__ Cre, const __nv_bfloat16* __restrict__ Cim, float* __restrict__ out,
             const __grid_constant__ Maps mp) {
    extern __shared__ __align__(1024) uint8_t smem[];
    const uint32_t sbase = SBASE + ((blockIdx.x & 1) << 24);
    if (smem_u32(smem) != sbase) __trap();
    const uint32_t bars = sbase + BAR_OFF;
    const int tid = threadIdx.x, lane = tid & 31;
    const int wg = __shfl_sync(0xffffffffu, tid >> 7, 0), warp = __shfl_sync(0xffffffffu, (tid >> 5) & 3, 0);
    if (tid < 96) {
        const int row = tid >> 2, bx = blockIdx.x & 127;
        const __nv_bfloat16* p = tid < 64 ? x : (tid < 80 ? Bre : Bim);
        pf_line(p + (tid < 64 ? bx * 16 + row : (bx >> 4) * 128 + (bx & 15) * 4 + (row & 3)) * 1024 + (tid & 3) * 64);
    }
    if (wg == 4 && warp == 1 && elect_one()) {
        asm volatile("prefetch.tensormap [%0];" :: "l"(&mp.BB) : "memory");
        asm volatile("prefetch.tensormap [%0];" :: "l"(&mp.X) : "memory");
        asm volatile("prefetch.tensormap [%0];" :: "l"(&mp.Xr) : "memory");
        for (int s = 0; s < RING; s++) mbar_init(EMPTY(s), 4);
        for (int i = 0; i < 14; i++) mbar_init(XB + 8 * i, i == 3 ? 129 : (i == 4 ? 2 : (i == 5 ? 8 : 1)));
        sts32(sbase + SACT_OFF, 0u); sts32(sbase + SACT_OFF + 4, 0u);
        asm volatile("fence.mbarrier_init.release.cluster;" ::: "memory");
        fence_async();
    }
    int cta = blockIdx.x;
    {
        unsigned int smid;
        asm volatile("mov.u32 %0, %%smid;" : "=r"(smid));
        if (full) {
            const int t = smid >> 1, u = (t - 32) / 7;
            const int g = t < 32 ? (t & 7) : (t < 60 ? t - 31 - 7 * u : 0), idx = t < 32 ? (t >> 3) : (t < 60 ? 4 + u : t - 58);
            const int lg = (0x73216540 >> (4 * g)) & 7;
            cta = ((t & ~1) == 60 || t > 65 ? 8 + 2 * t : 16 * lg + 2 * idx) + (smid & 1);
        }
    }
    const int cb = 2 * (cta >> 5) + (cta & 1), tc = (cta >> 1) & 15;
    const int db = 2 * ((cta >> 4) & 3) + (cta & 1), rc = 8 * ((cta >> 6) & 1) + ((cta >> 1) & 7);
    const long long t_start = clock64();
    if (cta >= NCTA) __trap();
    if (wg == 4 && warp == 0) {
        const bool one = elect_one();
        if (one) {
            for (int s = 0; s < RING; s++) mbar_init(FULL(s), 1);
            sts32(sbase + ROLE_OFF, cta);
            asm volatile("fence.mbarrier_init.release.cluster;" ::: "memory");
            fence_async();
        }
        __syncwarp();
        bar_arrive_n(0, 640);
        asm volatile("barrier.cluster.arrive.relaxed.aligned;" ::: "memory");
        if (one && cta < 128) {
            #pragma unroll
            for (int s = 0; s < RING; s++) {
                mbar_expect_tx(FULL(s), STGB);
                tma_load_4d(sbase + s * STGB, &mp.BB, s * 64, cb * 16, FULL(s));
                tma_load_3d(sbase + s * STGB + 16384, &mp.X, s * 64, tc * 8, 0, FULL(s));
                tma_load_3d(sbase + s * STGB + 24576, &mp.X, s * 64, tc * 8, 8, FULL(s));
            }
        }
        __syncwarp();
    } else {
        bar_sync_n(0, 640);
        asm volatile("barrier.cluster.arrive.relaxed.aligned;" ::: "memory");
    }
    if (wg >= 2 || cta >= 128) asm volatile("barrier.cluster.wait.acquire.aligned;" ::: "memory");
    if (wg == 4) {
        asm volatile("setmaxnreg.dec.sync.aligned.u32 24;");
        if (warp == 0) {
            const int prole = __shfl_sync(0xffffffffu, peer_role(sbase + ROLE_OFF), 0);
            const uint32_t rk = blockIdx.x & 1;
            if (cta >= 128) bar_arrive_n(DBAR + (prole >> 30), 64);
            const uint8_t* hs = reinterpret_cast<const uint8_t*>(g_h) + rc * 32 * 16384;
            if (cta < 128 && __all_sync(0xffffffffu, prole == (cta ^ 1))) {
                produce(mp, sbase, rk, cb, tc, db, rc);
            } else if (cta < 128) {
                uint32_t nw = 0;
                if (elect_one()) {
                    #pragma unroll 1
                    for (int it = RING; it < 64; it++) {
                        const int s = it % RING;
                        const uint32_t sa = sbase + s * STGB;
                        if (prole >= 128) mbar_arrive2(EMPTY(s));
                        mbar_wait_n(EMPTY(s), ((it / RING) - 1) & 1, nw);
                        mbar_expect_tx(FULL(s), STGB);
                        if (it < 32) {
                            tma_load_4d(sa, &mp.BB, (it & 15) * 64, cb * 16 + (it >> 4) * 8, FULL(s));
                            tma_load_3d(sa + 16384, &mp.X, (it & 15) * 64, tc * 8, 0, FULL(s));
                            tma_load_3d(sa + 24576, &mp.X, (it & 15) * 64, tc * 8, 8, FULL(s));
                        } else {
                            const CUtensorMap* cm = (it & 8) ? &mp.Cim : &mp.Cre;
                            tma_load_5d(sa + 16384, cm, (it & 7) * 128 + (it & 16) * 4, db * 4, FULL(s));
                            tma_load_5d(sa + 24576, cm, (it & 7) * 128 + (it & 16) * 4, db * 4 + 32, FULL(s));
                            mbar_wait_n(HOK((it >> 3) & 3), 0, nw);
                            bulk_load(sa, hs + (it - 32) * 16384, 16384, FULL(s));
                        }
                    }
                }
            } else if (cta >= 128 && prole < 128 && lane == 0) {
                mbar_arrive2(EMPTY(RING - 1));
                #pragma unroll 1
                for (int p = 0; p < 8; p++) mbar_wait(EMPTY(RING - 1), p & 1);
            }
        } else if (warp == 1) {
            if (cta < 130) {
                #pragma unroll 1
                for (int i = lane; i < 128; i += 32) {
                    const int p = (cb & 7) * 128 + i;
                    const float dt = bf16r(expf(__bfloat162float(log_dt[p]))), lr = __bfloat162float(lam_re[p]), li = __bfloat162float(lam_im[p]);
                    const float er = expf(dt * lr), den = lr * lr + li * li;
                    float sn, cs; sincospif(dt * li * 0.31830988618379067154f, &sn, &cs);
                    cs *= er; sn *= er;
                    sts128(sbase + LAM_OFF + i * 16, __float_as_uint(cs), __float_as_uint(swp ? -sn : sn),
                           __float_as_uint(__fdividef((cs - 1.f) * lr + sn * li, den)), __float_as_uint(__fdividef(sn * lr - (cs - 1.f) * li, den)));
                    float2 l = make_float2(cs, swp ? -sn : sn);
                    l = cmul(l, l); l = cmul(l, l); l = cmul(l, l); l = cmul(l, l);
                    const float2 l2 = cmul(l, l);
                    sts128(sbase + LAM_OFF + 2048 + i * 16, __float_as_uint(l.x), __float_as_uint(l.y), __float_as_uint(l2.x), __float_as_uint(l2.y));
                }
                __syncwarp();
                if (lane == 0) mbar_arrive(EPB);
                mbar_wait(EPB, 0);
                const unsigned int epoch = lds32(sbase + EPO_OFF);
                const bool one = elect_one();
                if (one) {
                    while (clock64() - t_start < TTAB) { __nanosleep(100); }
                    mbar_expect_tx(X1B(0), 16384 + 2048 + 10240);
                    bulk_load(sbase + B16F_OFF, g_img.b16f, 2048, X1B(0));
                    bulk_load(sbase + R2, cta < 2 ? g_img.m4re[cta] : g_img.h[cta & 1].m4, 8192, X1B(0));
                    bulk_load(sbase + R2 + 8192, g_img.h[cta & 1].b16i, 2048, X1B(0));
                }
                __syncwarp();
                if (cta < 128) bar_sync_n(GBAR, 288);
                if (one) {
                    if (cta < 128) { red_release(&g_cnt1); }
                    mbar_expect_tx(X1B(1), 16384);
                    wait_counter(&g_cnt1, 128u * epoch);
                    #pragma unroll 1
                    for (int i = 0; i < 4; i++) { bulk_load(sbase + R1 + i * 8192, g_X1 + (cta & 127) * 2048 + i * 512, 8192, X1B(i >> 1)); delay(PCL); }
                }
                #pragma unroll 1
                for (int i = 0; i < 4; i++) {
                    if (one) load_w(mp.W, sbase, cta, i);
                    __syncwarp();
                    if (i != 2) bar_sync_n(LBAR + min(i, 2), 160);
                }
                if (one) {
                    red_release(cta < 128 ? &g_cnt2 : &g_cnt3);
                    if (cta < 128) {
                        const uint8_t* img = reinterpret_cast<const uint8_t*>(g_X2) + (8 * rc + db) * X2_IMG;
                        mbar_expect_tx(ZOK, 32768 - 256);
                        wait_counter(&g_cnt2, 128u * epoch);
                        bulk_load(sbase + R1, img, 1024, ZOK);
                        bulk_load(sbase + R1 + 16384, img + X2_IMG / 2, 1024, ZOK);
                        #pragma unroll 1
                        for (int k = 0; k < NZ; k++) {
                            constexpr int ZP = 32768 / NZ;
                            const int o = (k * ZP) & 16383, h = (k * ZP) >> 14, o2 = o ? o : 1152;
                            bulk_load(sbase + R1 + h * 16384 + o2, img + h * (X2_IMG / 2) + o2, o + ZP - o2, ZOK);
                            const uint32_t c = clk32();
                            while ((int)(clk32() - c) < PCZ && !lds32(sbase + SACT_OFF + 4)) { }
                        }
                    }
                }
            }
        } else if (warp == 2) {
            if (cta < 128) {
                const uint8_t* bp = reinterpret_cast<const uint8_t*>((lane & 16) ? Bim : Bre) + (cb * 128 + tc * 4 + ((lane >> 2) & 3)) * 2048 + (lane & 3) * 128;
                while (clock64() - t_start < TXT) { }
                if (elect_one()) {
                    mbar_expect_tx(XB, 32768 + 256);
                    bulk_load(sbase + GATE_OFF, gate_w + db * 64, 128, XB);
                    bulk_load(sbase + GATE_OFF + 128, gate_w + db * 64 + 512, 128, XB);
                    #pragma unroll
                    for (int i = 0; i < 8; i++) tma_load_2d(sbase + R0 + i * 4096, &mp.Xr, rc * 1024 + db * 64 + (i >> 2) * 512, (i & 3) * 32, XB);
                }
                __syncwarp();
                pf_line(bp + 1024); pf_line(bp + 1536);
                if ((cta & 63) < 12) pf_line(reinterpret_cast<const uint8_t*>(&g_img) + (cta & 63) * 4096 + lane * 128);
                while (clock64() - t_start < PFW) { }
                const uint32_t wrow = (((cta & 1) ? 128 - (cta >> 1) : (cta >> 1)) + 128 * (lane >> 1)) & 2047;
                const uint8_t* wp = reinterpret_cast<const uint8_t*>(lane & 1 ? w_i : w_r) + wrow * 1026u;
                #pragma unroll 1
                for (int k = 0; k < 9; k++) { pf_line(wp + (k < 8 ? k * 128 : 1024)); __nanosleep(200); }
                while (clock64() - t_start < PFB) { }
                #pragma unroll 1
                for (int k = 0; k < 16; k += 4) { pf_line(bp + 64 * 2048 + k * 128); __nanosleep(200); }
                const uint8_t* cp = reinterpret_cast<const uint8_t*>((lane & 16) ? Cim : Cre) + (cta * 8 + (lane & 7)) * 2048 + (lane & 8) * 32;
                #pragma unroll 1
                for (int k = 0; k < 8; k++) {
                    while (clock64() - t_start < PFC + k * PFCS) { __nanosleep(100); }
                    pf_line(cp + (k & 3) * 512 + (k >> 2) * 128);
                }
            }
        } else {
            unsigned int epoch = 0;
            if (cta >= 128) bar_sync_n(DBAR, 64);
            if (lane == 0) {
                epoch = atomicAdd(&g_ticket, 1u);
                epoch = (full ? epoch / NCTA : epoch / 130u) + 1u;
                sts32(sbase + EPO_OFF, epoch);
                mbar_arrive(EPB);
            }
            __syncwarp();
            if (cta < 128) {
                #pragma unroll 1
                for (int i = 0; i < 4; i++) {
                    bar_sync_n(HBAR + i, 160);
                    if (lane == 0) {
                        red_release(&g_cnth(i));
                        wait_counter(&g_cnth(i), 128u * epoch);
                        mbar_arrive(HOK(i));
                    }
                    __syncwarp();
                }
                if (lane == 0) {
                    mbar_expect_tx(XB, 32768);
                    #pragma unroll 1
                    for (int i = 0; i < 8; i++) { tma_load_2d(sbase + R0 + i * 4096, &mp.Xr, rc * 1024 + db * 64 + (i >> 2) * 512, (i & 3) * 32, XB); __nanosleep(150); }
                }
            } else if (cta >= 130 && lane == 0) {
                #pragma unroll 1
                for (int i = 0; i < (1 << 22); i++) {
                    __nanosleep(200);
                    if ((int)(*reinterpret_cast<volatile unsigned int*>(&g_ticket) - NCTA * epoch) >= 0) break;
                }
            }
        }
    } else if (wg >= 2) {
      if (cta < 128) {
          float2 w1, w32;
          sincospif((float)(16 * tid128() + rc) * (1.f / 1024.f), &w1.y, &w1.x);
          w32 = cmul(w1, w1); w32 = cmul(w32, w32); w32 = cmul(w32, w32); w32 = cmul(w32, w32); w32 = cmul(w32, w32);
          gen_dft(sbase + R1, tid128(), w1, wg == 2 ? make_float2(1.f, 0.f) : make_float2(w32.x, -w32.y), 4 * wg - 8, 4 * wg - 4, 0.5f);
          fence_async();
          bar_sync_n(wg, 128);
          mbar_wait(XB, 0);
          fft_p1(sbase, bars, wg - 2, rc, db, (uint32_t)t_start + P1END);
          bar_arrive_n(GBAR, 288);
      }
      if (wg == 3) {
        asm volatile("setmaxnreg.inc.sync.aligned.u32 120;");
        {
            if (cta < 128) {
                mbar_wait(EPB, 0);
                #pragma unroll 1
                for (int half = 0; half < 2; half++) {
                    const int t1 = tid128(), ch = t1 >> 1, hf = t1 & 1, p = cb * 128 + half * 64 + ch;
                    if (half) {
                        mbar_wait(X1B(0), 0);
                        float s = 0.f;
                        #pragma unroll
                        for (int i = 0; i < 16; i++) s += __ldcg(&g_gp[(16 * rc + i) * 128 + t1]);
                        const float gv = bf16r(__fdividef(1.f, 1.f + expf(-bf16r(s))));
                        sts32(sbase + GATE_OFF + 4 * t1, pack2(gv, 1.f - gv));
                    }
                    const uint4 pm = lds128(sbase + LAM_OFF + (half * 64 + ch) * 16);
                    const uint32_t sg = (uint32_t)swp << 31;
                    float2 lam = make_float2(__uint_as_float(pm.x), __uint_as_float(pm.y ^ sg));
                    float cr = __uint_as_float(pm.z), ci = __uint_as_float(pm.w);
                    const uint4 pp = lds128(sbase + LAM_OFF + 2048 + (half * 64 + ch) * 16);
                    const float2 l16 = make_float2(__uint_as_float(pp.x), __uint_as_float(pp.y ^ sg)), l32 = make_float2(__uint_as_float(pp.z), __uint_as_float(pp.w ^ sg));
                    const float2 l64 = cmul(l32, l32), l128 = cmul(l64, l64), l256 = cmul(l128, l128);
                    const unsigned int par = lds32(sbase + EPO_OFF) & 1u;
                    if (__float_as_uint(l256.x) == 0x9e3779b9u) sts32(sbase + SACT_OFF + 4, 0u);
                    bar_sync_n(DBAR, 384);
                    uint2 ur[16], ui[16];
                    #pragma unroll
                    for (int r = 15; r >= 0; r--) { ur[r] = lds64(sbase + R0 + r * 1024 + t1 * 8); ui[r] = lds64(sbase + R0 + 16384 + r * 1024 + t1 * 8); }
                    float2 e[4], E0;
                    e[0] = make_float2(bflo(ur[15].x), bflo(ui[15].x));
                    e[1] = cfma(l16, e[0], make_float2(bfhi(ur[15].x), bfhi(ui[15].x)));
                    e[2] = cfma(l16, e[1], make_float2(bflo(ur[15].y), bflo(ui[15].y)));
                    e[3] = cfma(l16, e[2], make_float2(bfhi(ur[15].y), bfhi(ui[15].y)));
                    E0.x = __shfl_xor_sync(0xffffffffu, e[3].x, 1); E0.y = __shfl_xor_sync(0xffffffffu, e[3].y, 1);
                    const uint2* src = reinterpret_cast<const uint2*>(g_agg) + (tc - 1 - hf) * P_DIM + p;
                    const int nv = tc - hf;
                    uint2 v[8];
                    {
                        const bf2 c2 = asbf2(pack2(cr, cr)), n2 = asbf2(pack2(-cr, -cr)), s2 = asbf2(pack2(-ci, -ci));
                        #pragma unroll
                        for (int r = 15; r >= 0; r--) {
                            if (r == 8) {
                                boundary();
                                #pragma unroll
                                for (int i = 0; i < 8; i++) {
                                    v[i] = make_uint2(par, par);
                                    if (2 * i < nv) asm volatile("ld.relaxed.gpu.global.v2.u32 {%0, %1}, [%2];" : "=r"(v[i].x), "=r"(v[i].y) : "l"(src - i * 2 * P_DIM) : "memory");
                                }
                                #pragma unroll
                                for (int q = r; q >= 0; q--) asm volatile("" : "+r"(ur[q].x), "+r"(ur[q].y), "+r"(ui[q].x), "+r"(ui[q].y) :: "memory");
                            }
                            const bf2 a = asbf2(ur[r].x), b = asbf2(ui[r].x), c = asbf2(ur[r].y), d = asbf2(ui[r].y);
                            ur[r].x = asu32(__hfma2(c2, a, __hmul2(s2, b))); ui[r].x = asu32(__hfma2(n2, b, __hmul2(s2, a)));
                            ur[r].y = asu32(__hfma2(c2, c, __hmul2(s2, d))); ui[r].y = asu32(__hfma2(n2, d, __hmul2(s2, c)));
                            asm volatile("" : "+r"(ur[r].x), "+r"(ur[r].y), "+r"(ui[r].x), "+r"(ui[r].y) :: "memory");
                        }
                    }
                    __syncwarp();
                    if (lane == 0) mbar_arrive2(R0F);
                    #pragma unroll 1
                    for (int spins = 0; spins < (1 << 20); spins++) {
                        uint32_t bad = 0;
                        #pragma unroll
                        for (int i = 0; i < 8; i++) bad |= (v[i].x ^ par) | (v[i].y ^ par);
                        if (!__any_sync(0xffffffffu, bad & 1u)) break;
                        #pragma unroll
                        for (int i = 0; i < 8; i++)
                            if (2 * i < nv) asm volatile("ld.relaxed.gpu.global.v2.u32 {%0, %1}, [%2];" : "+r"(v[i].x), "+r"(v[i].y) : "l"(src - i * 2 * P_DIM) : "memory");
                    }
                    if (t1 == 0) { sts32(sbase + SACT_OFF, 1u); }
                    float2 H = make_float2(__uint_as_float(v[7].x), __uint_as_float(v[7].y));
                    #pragma unroll
                    for (int i = 6; i >= 0; i--) H = cfma(l256, H, make_float2(__uint_as_float(v[i].x), __uint_as_float(v[i].y)));
                    if (hf) H = cmul(H, l128);
                    H.x += __shfl_xor_sync(0xffffffffu, H.x, 1); H.y += __shfl_xor_sync(0xffffffffu, H.y, 1);
                    float2 st[4];
                    st[0] = hf ? cfma(l64, H, E0) : H;
                    st[1] = cfma(l16, st[0], e[0]); st[2] = cfma(l32, st[0], e[1]); st[3] = cfma(l16, cmul(l32, st[0]), e[2]);
                    const bf2 gr0 = asbf2(pack2(cr * st[0].x - ci * st[0].y, cr * st[1].x - ci * st[1].y)), gr1 = asbf2(pack2(cr * st[2].x - ci * st[2].y, cr * st[3].x - ci * st[3].y));
                    const bf2 gi0 = asbf2(pack2(-ci * st[0].x - cr * st[0].y, -ci * st[1].x - cr * st[1].y)), gi1 = asbf2(pack2(-ci * st[2].x - cr * st[2].y, -ci * st[3].x - cr * st[3].y));
                    uint2* dst = reinterpret_cast<uint2*>(g_h + (half * 16 + cb) * 1024 + tc * 64) + t1;
                    lam.y = -lam.y;
                    float2 z = lam;
                    uint32_t pw[16], tp = clk32() + warp * (PCR / 2);
                    #pragma unroll
                    for (int r = 0; r < 16; r++) {
                        pw[r] = pack2(z.x, z.y); z = cmul(z, lam);
                        const bf2 pr = __low2bfloat162(asbf2(pw[r])), pi = __high2bfloat162(asbf2(pw[r]));
                        if (!(r & 1)) pace(tp, 2 * PCR);
                        __stcg(dst + r * 65536, make_uint2(asu32(__hfma2(pr, gr0, __hfma2(pi, neg2(gi0), asbf2(ur[r].x)))), asu32(__hfma2(pr, gr1, __hfma2(pi, neg2(gi1), asbf2(ur[r].y))))));
                    }
                    bar_arrive_n(HBAR + 2 * half, 160);
                    if (t1 == 0) { sts32(sbase + SACT_OFF, 0u); }
                    #pragma unroll
                    for (int r = 0; r < 16; r++) {
                        const bf2 pr = __low2bfloat162(asbf2(pw[r])), pi = __high2bfloat162(asbf2(pw[r]));
                        if (!(r & 1)) pace(tp, 2 * PCH);
                        __stcg(dst + r * 65536 + 16384, make_uint2(asu32(__hfma2(pr, gi0, __hfma2(pi, gr0, asbf2(ui[r].x)))), asu32(__hfma2(pr, gi1, __hfma2(pi, gr1, asbf2(ui[r].y))))));
                    }
                    bar_arrive_n(HBAR + 2 * half + 1, 160);
                }
            }
        }
      } else {
        asm volatile("setmaxnreg.inc.sync.aligned.u32 144;");
        if (cta < 130) {
            fft_p2(sbase, bars, cta, w_r, w_i);
            bar_sync_n(LBAR + 2, 160);
            if (cta < 128) {
                const int j = tid128();
                if (j < 16) {
                    const uint2 d0 = __ldg(reinterpret_cast<const uint2*>(dskip) + db * 16 + j), d1 = __ldg(reinterpret_cast<const uint2*>(dskip) + db * 16 + 128 + j);
                    sts128(sbase + DSK_OFF + j * 16, d0.x, d0.y, d1.x, d1.y);
                }
                mbar_wait(HOK(2), 0);
                const float gv = bflo(lds32(sbase + GATE_OFF + 4 * j));
                gen_dft(sbase + R2, j, cis(16 * j + rc), make_float2(gv * (1.f / 1048576.f), 0.f), 0, 8, gv * (1.f / 1048576.f));
                const uint8_t* img = reinterpret_cast<const uint8_t*>(g_X2) + (8 * rc + db) * X2_IMG;
                if ((j >> 4) == 4) {
                    wait_counter(&g_cnt3, 2u * lds32(sbase + EPO_OFF));
                    const float cs = g_img.cs[0][4 * rc][0], sn = g_img.cs[0][4 * rc][1];
                    const uint4* s4 = reinterpret_cast<const uint4*>(img + ((j >> 3) & 1) * (X2_IMG / 2) + 16384) + (j & 7);
                    const uint4 a = __ldcg(s4), b = __ldcg(s4 + 64);
                    sts128(sbase + R1 + ((j >> 3) & 1) * 16384 + 1024 + (j & 7) * 16,
                           pack2(cs * bflo(a.x) - sn * bflo(b.x), cs * bfhi(a.x) - sn * bfhi(b.x)), pack2(cs * bflo(a.y) - sn * bflo(b.y), cs * bfhi(a.y) - sn * bfhi(b.y)),
                           pack2(cs * bflo(a.z) - sn * bflo(b.z), cs * bfhi(a.z) - sn * bfhi(b.z)), pack2(cs * bflo(a.w) - sn * bflo(b.w), cs * bfhi(a.w) - sn * bfhi(b.w)));
                }
                fence_async();
                mbar_arrive(ZOK);
            }
        }
      }
    } else {
        if (cta < 128) {
            {
                const int w8 = tid >> 5;
                if (w8 == 0) pf_line(((lane & 16) ? Bim : Bre) + (cb * 128 + tc * 4 + ((lane >> 2) & 3)) * 1024 + (4 + (lane & 3)) * 64);
                else if (w8 < 3) pf_line(x + (cta * 16 + (lane >> 1)) * 1024 + (2 + 2 * w8 + (lane & 1)) * 64);
            }
            float A[64];
            #pragma unroll
            for (int i = 0; i < 64; i++) A[i] = 0.f;
            gemm_main(A, sbase, wg, warp, lane, cb, tc, swp);
            const int ln = tid128() & 31, row = 64 * wg + 16 * warp + (ln >> 2);
            if (wg == 0) bar_arrive_n(TBAR, 256);
            mbar_wait(ZOK, 0);
            float om[2];
            om[0] = bfhi(lds32(sbase + GATE_OFF + 4 * row)); om[1] = bfhi(lds32(sbase + GATE_OFF + 4 * row + 32));
            wgmma_wait<0>();
            reg_fence<64>(A);
            #pragma unroll
            for (int i = 0; i < 32; i++) { const float o = om[(i >> 1) & 1], t = o * A[i], u = A[i + 32]; A[i] = fmaf(o, u, t); A[i + 32] = fmaf(-o, u, t); }
            constexpr uint32_t s16 = SBASE / 16;
            wgmma_fence();
            #pragma unroll
            for (int ks = 0; ks < 8; ks++)
                ss128<0, 1>(A, mkd(s16 + wg * 512, R2 + (ks >> 2) * 16384 + (ks & 3) * 32, 16, 1024, 1), mkd(s16, R1 + ks * 2048, 16384, 1024, 1));
            wgmma_commit();
            if (wg == 0) bar_arrive_n(TBAR + 1, 256);
            float* o = out + (size_t)(16 * row + rc) * 1024 + db * 64 + 4 * (ln & 3);
            mbar_wait(XB, 1);
            wgmma_wait<0>();
            reg_fence<64>(A);
            #pragma unroll
            for (int J = 0; J < 4; J++) {
                if (J) boundary();
                const uint4 dk = lds128(sbase + DSK_OFF + (4 * J + (ln & 3)) * 16);
                #pragma unroll
                for (int h = 0; h < 2; h++) {
                    const uint32_t xo = sbase + R0 + (row + 8 * h) * 128 + (ln & 1) * 8 + (((2 * J + ((ln >> 1) & 1)) ^ (ln >> 2)) << 4);
                    uint2 p = lds64(xo), s = lds64(xo + 16384);
                    p.x = hmul2bf(p.x, dk.x); p.y = hmul2bf(p.y, dk.y); s.x = hmul2bf(s.x, dk.z); s.y = hmul2bf(s.y, dk.w);
                    const float* a = A + 8 * J + 2 * h;
                    float4 u = make_float4(fmaf(om[h], bflo(p.x), a[0] + a[32]), fmaf(om[h], bfhi(p.x), a[1] + a[33]), fmaf(om[h], bflo(p.y), a[4] + a[36]), fmaf(om[h], bfhi(p.y), a[5] + a[37]));
                    float4 v = make_float4(fmaf(om[h], bflo(s.x), a[0] - a[32]), fmaf(om[h], bfhi(s.x), a[1] - a[33]), fmaf(om[h], bflo(s.y), a[4] - a[36]), fmaf(om[h], bfhi(s.y), a[5] - a[37]));
                    __stcs(reinterpret_cast<float4*>(o + h * 131072 + J * 16), u);
                    __stcs(reinterpret_cast<float4*>(o + h * 131072 + J * 16 + 512), v);
                }
            }
        }
    }
}

typedef CUresult (*PFN_encodeTiled_t)(CUtensorMap*, CUtensorMapDataType, cuuint32_t, void*, const cuuint64_t*, const cuuint64_t*,
                                      const cuuint32_t*, const cuuint32_t*, CUtensorMapInterleave, CUtensorMapSwizzle,
                                      CUtensorMapL2promotion, CUtensorMapFloatOOBfill);

static CUresult make_map(PFN_encodeTiled_t enc, CUtensorMap* m, int rank, const void* ptr, const cuuint64_t* dims, const cuuint64_t* strides, const cuuint32_t* box) {
    cuuint32_t es[5] = {1, 1, 1, 1, 1};
    return enc(m, CU_TENSOR_MAP_DATA_TYPE_BFLOAT16, rank, (void*)ptr, dims, strides, box, es, CU_TENSOR_MAP_INTERLEAVE_NONE, CU_TENSOR_MAP_SWIZZLE_128B,
        CU_TENSOR_MAP_L2_PROMOTION_L2_128B, CU_TENSOR_MAP_FLOAT_OOB_FILL_NONE);
}
static void make_map_2d(PFN_encodeTiled_t enc, CUtensorMap* m, const void* ptr, int rows, int cols, int box_rows) {
    cuuint64_t dims[2] = {(cuuint64_t)cols, (cuuint64_t)rows};
    cuuint64_t strides[1] = {(cuuint64_t)cols * 2};
    cuuint32_t box[2] = {64, (cuuint32_t)box_rows};
    make_map(enc, m, 2, ptr, dims, strides, box);
}

extern "C" void kernel_launch(void* const* d_in, const int* in_sizes, int n_in, void* d_out, int out_size) {
    const __nv_bfloat16* x = (const __nv_bfloat16*)d_in[0];
    const __nv_bfloat16* w_r = (const __nv_bfloat16*)d_in[1];
    const __nv_bfloat16* w_i = (const __nv_bfloat16*)d_in[2];
    const __nv_bfloat16* lam_re = (const __nv_bfloat16*)d_in[4];
    const __nv_bfloat16* lam_im = (const __nv_bfloat16*)d_in[5];
    const __nv_bfloat16* B_re = (const __nv_bfloat16*)d_in[6];
    const __nv_bfloat16* B_im = (const __nv_bfloat16*)d_in[7];
    const __nv_bfloat16* C_re = (const __nv_bfloat16*)d_in[8];
    const __nv_bfloat16* C_im = (const __nv_bfloat16*)d_in[9];
    const __nv_bfloat16* log_dt = (const __nv_bfloat16*)d_in[10];
    const __nv_bfloat16* dskip = (const __nv_bfloat16*)d_in[11];
    const __nv_bfloat16* gate_w = (const __nv_bfloat16*)d_in[12];

    static PFN_encodeTiled_t enc = nullptr;
    static Maps mp;
    static int grid = 130, swp = 0, copyB = 0;
    static void* bcopy = nullptr;
    static const void* key[7] = {nullptr, nullptr, nullptr, nullptr, nullptr, nullptr, nullptr};
    if (!enc) {
        cudaDriverEntryPointQueryResult qres;
        cudaGetDriverEntryPoint("cuTensorMapEncodeTiled", (void**)&enc, cudaEnableDefault, &qres);
        cudaFuncSetAttribute(fused_kernel<true>, cudaFuncAttributeMaxDynamicSharedMemorySize, TOT_SMEM);
        cudaFuncSetAttribute(fused_kernel<false>, cudaFuncAttributeMaxDynamicSharedMemorySize, TOT_SMEM);
        int dev = 0, nsm = 0;
        cudaGetDevice(&dev);
        cudaDeviceGetAttribute(&nsm, cudaDevAttrMultiProcessorCount, dev);
        grid = nsm == NCTA ? NCTA : 130;
    }
    if (key[0] != x || key[1] != B_re || key[2] != B_im || key[3] != C_re || key[4] != C_im || key[5] != w_r || key[6] != w_i) {
        cudaGetSymbolAddress(&bcopy, g_Bcopy);
        {
            const uintptr_t a = (uintptr_t)B_re, b = (uintptr_t)B_im;
            swp = b < a;
            cuuint64_t dims[4] = {D_DIM, 8, 2, P_DIM / 8};
            cuuint64_t strides[3] = {D_DIM * 2, (cuuint64_t)(swp ? a - b : b - a), D_DIM * 2 * 8};
            cuuint32_t box[4] = {64, 8, 2, 8};
            copyB = strides[1] == 0 || (strides[1] & 15) || strides[1] >= (1ull << 39);
            if (!copyB) copyB = make_map(enc, &mp.BB, 4, swp ? B_im : B_re, dims, strides, box) != CUDA_SUCCESS;
            if (copyB) {
                swp = 0; strides[1] = (cuuint64_t)P_DIM * D_DIM * 2;
                make_map(enc, &mp.BB, 4, bcopy, dims, strides, box);
            }
        }
        {
            cuuint64_t dims[3] = {D_DIM, S_LEN / 16, 16};
            cuuint64_t strides[2] = {D_DIM * 2 * 16, D_DIM * 2};
            cuuint32_t box[3] = {64, 8, 8};
            make_map(enc, &mp.X, 3, x, dims, strides, box);
        }
        make_map_2d(enc, &mp.Xr, x, S_LEN / 16, D_DIM * 16, 32);
        {
            cuuint64_t dims[5] = {P_DIM, 2, 4, 2, D_DIM / 16};
            cuuint64_t strides[4] = {P_DIM * 2, P_DIM * 2 * 4, P_DIM * 2 * 2, P_DIM * 2 * 16};
            cuuint32_t box[5] = {64, 2, 4, 2, 4};
            make_map(enc, &mp.Cre, 5, C_re, dims, strides, box);
            make_map(enc, &mp.Cim, 5, C_im, dims, strides, box);
        }
        for (int a = 0; a < 2; a++) {
            cuuint64_t dims[3] = {128 * 513 - 448, 8, 16};
            cuuint64_t strides[2] = {128, 128 * 513 * 2};
            cuuint32_t box[3] = {64, 8, 4};
            make_map(enc, &mp.W[a], 3, a ? w_i : w_r, dims, strides, box);
        }
        key[5] = w_r; key[6] = w_i;
        key[0] = x; key[1] = B_re; key[2] = B_im; key[3] = C_re; key[4] = C_im;
    }
    if (copyB) {
        cudaMemcpyAsync(bcopy, B_re, (size_t)P_DIM * D_DIM * 2, cudaMemcpyDeviceToDevice, cudaStreamPerThread);
        cudaMemcpyAsync((char*)bcopy + (size_t)P_DIM * D_DIM * 2, B_im, (size_t)P_DIM * D_DIM * 2, cudaMemcpyDeviceToDevice, cudaStreamPerThread);
    }
    (grid == NCTA ? fused_kernel<true> : fused_kernel<false>)<<<grid, 640, TOT_SMEM, cudaStreamPerThread>>>(x, B_re, B_im, swp, w_r, w_i, lam_re, lam_im, log_dt, dskip, gate_w,
        C_re, C_im, (float*)d_out, mp);
}
```

```cpp
#include <cuda_runtime.h>
#include <cuda_bf16.h>
#include <cuda.h>
#include <stdint.h>

#define S_LEN 2048
#define D_DIM 1024
#define P_DIM 1024

namespace ct {
constexpr double PI = 3.14159265358979323846264338327950288;
constexpr double tsin(double x) { double term = x, sum = x; for (int i = 1; i < 12; i++) { term *= -x * x / ((2 * i) * (2 * i + 1)); sum += term; } return sum; }
constexpr double tcos(double x) { double term = 1, sum = 1; for (int i = 1; i < 12; i++) { term *= -x * x / ((2 * i - 1) * (2 * i)); sum += term; } return sum; }
struct CosTab { double v[513]; };
constexpr CosTab make_cos() {
    CosTab t{};
    for (int m = 0; m <= 512; m++) t.v[m] = m == 512 ? 0.0 : (m <= 256 ? tcos(2 * PI * m / 2048.0) : tsin(2 * PI * (512 - m) / 2048.0));
    return t;
}
constexpr CosTab COS = make_cos();
constexpr double cos2048(int m) {
    m &= 2047;
    if (m > 1024) m = 2048 - m;
    if (m > 512) return -COS.v[1024 - m];
    return COS.v[m];
}
constexpr double sin2048(int m) { return cos2048(m - 512); }
constexpr unsigned short bf16bits(double v) {
    if (v == 0.0) return 0;
    unsigned short s = 0;
    if (v < 0) { s = 0x8000; v = -v; }
    int e = 0;
    while (v >= 2.0) { v *= 0.5; e++; }
    while (v < 1.0) { v *= 2.0; e--; }
    double r = v * 128.0;
    int ri = (int)r;
    double fr = r - ri;
    if (fr > 0.5 || (fr == 0.5 && (ri & 1))) ri++;
    if (ri == 256) { ri = 128; e++; }
    return (unsigned short)(s | ((e + 127) << 7) | (ri - 128));
}
constexpr int kmaj(int row, int k, int sbo) { return ((row >> 3) * sbo + (k >> 3) * 128 + (row & 7) * 16 + (k & 7) * 2) >> 1; }
constexpr double rot(int ro, int ri, int a) { return ro == ri ? cos2048(a) : (ro == 0 ? sin2048(a) : -sin2048(a)); }
constexpr int bin(int n) { return (n & 8) | ((n & 3) << 1) | ((n >> 2) & 1); }
constexpr int bout(int n) { return ((n & 2) << 2) | ((n >> 1) & 6) | (n & 1); }
struct Half {
    unsigned short m4[4096];
    unsigned short b16i[1024];
    unsigned short tw[2][128][8];
};
struct Img { unsigned short b16f[1024]; Half h[2]; float cs[16][128][2]; unsigned short m4re[2][4096]; };
constexpr Img make_img() {
    Img t{};
    for (int n = 0; n < 32; n++) for (int k = 0; k < 32; k++) t.b16f[kmaj(n, k, 512)] = bf16bits(rot(((n >> 4) ^ (n >> 3)) & 1, k >> 4, bin(k & 15) * (n & 15) * 128));
    for (int r = 0; r < 16; r++) for (int j = 0; j < 128; j++) { t.cs[r][j][0] = (float)cos2048(16 * j + r); t.cs[r][j][1] = (float)sin2048(16 * j + r); }
    for (int ke = 0; ke < 2; ke++) {
        Half& h = t.h[ke];
        for (int n = 0; n < 32; n++) for (int k = 0; k < 32; k++) h.b16i[kmaj(n, k, 512)] = bf16bits(rot(n >> 4, ((k >> 4) ^ (k >> 3)) & 1, -bout(n & 15) * (k & 15) * 128));
        for (int m = 0; m < 64; m++) for (int k = 0; k < 64; k++) {
            int a = 4 * (m >> 3) + (m & 3), ro = (m >> 2) & 1, kx = 8 * (k >> 4) + (k & 7), ri = (k >> 3) & 1;
            h.m4[kmaj(m, k, 1024)] = bf16bits(rot(ro, ri, -a * (ke + 2 * kx) * 32));
            t.m4re[ke][kmaj(m, k, 1024)] = ro ? 0 : h.m4[kmaj(m, k, 1024)];
        }
        for (int tid = 0; tid < 128; tid++) {
            int kap = ke + 2 * (tid >> 2), q = tid & 3;
            for (int hb = 0; hb < 2; hb++) for (int e = 0; e < 2; e++) {
                int n = 8 * hb + 2 * q + e;
                h.tw[0][tid][4 * hb + e] = bf16bits(cos2048(2 * bin(n) * kap));  h.tw[0][tid][4 * hb + 2 + e] = bf16bits(-sin2048(2 * bin(n) * kap));
                h.tw[1][tid][4 * hb + e] = bf16bits(cos2048(2 * bout(n) * kap)); h.tw[1][tid][4 * hb + 2 + e] = bf16bits(sin2048(2 * bout(n) * kap));
            }
        }
    }
    return t;
}
}
__device__ __align__(128) const ct::Img g_img = ct::make_img();

#define SBASE 0x400u
#define RING 4
#define STGB 32768
#define R0 (4 * 32768)
#define R1 (5 * 32768)
#define R2 (6 * 32768)
#define B16F_OFF (7 * 32768)
#define BAR_OFF (B16F_OFF + 2048)
#define GATE_OFF (BAR_OFF + 256)
#define DSK_OFF (GATE_OFF + 512)
#define TOT_SMEM (DSK_OFF + 256)
#define NCTA 132
#define X2_IMG 36864

__device__ __align__(1024) uint4 g_X1[128 * 2048];
__device__ __align__(1024) uint4 g_X2[128 * X2_IMG / 16];
__device__ __align__(128) float g_gp[256 * 128];
__device__ __align__(1024) uint4 g_h[16 * 32 * 1024];
__device__ __align__(128) unsigned long long g_agg[16 * P_DIM];
__device__ __align__(128) unsigned int g_cnt[8 * 32];
__device__ __align__(1024) __nv_bfloat16 g_Bcopy[2 * P_DIM * D_DIM];
#define g_ticket g_cnt[0]
#define g_cnt1 g_cnt[32]
#define g_cnt2 g_cnt[64]
#define g_cnt3 g_cnt[224]
#define g_cnth(i) g_cnt[96 + 32 * (i)]


__device__ __forceinline__ float bf16r(float v) { return __bfloat162float(__float2bfloat16_rn(v)); }
__device__ __forceinline__ float2 cmul(float2 a, float2 b) { return make_float2(a.x * b.x - a.y * b.y, a.x * b.y + a.y * b.x); }
__device__ __forceinline__ float2 cfma(float2 a, float2 b, float2 c) {
    float re = fmaf(a.x, b.x, c.x); re = fmaf(-a.y, b.y, re);
    float im = fmaf(a.x, b.y, c.y); im = fmaf(a.y, b.x, im);
    return make_float2(re, im);
}
__device__ __forceinline__ uint32_t smem_u32(const void* p) { return (uint32_t)__cvta_generic_to_shared(p); }
__device__ __forceinline__ void bar_sync_n(int id, int n) { asm volatile("bar.sync %0, %1;" :: "r"(id), "r"(n) : "memory"); }
__device__ __forceinline__ void bar_arrive_n(int id, int n) { asm volatile("bar.arrive %0, %1;" :: "r"(id), "r"(n) : "memory"); }
__device__ __forceinline__ uint32_t pack2(float lo, float hi) { uint32_t r; asm("cvt.rn.bf16x2.f32 %0, %1, %2;" : "=r"(r) : "f"(hi), "f"(lo)); return r; }
__device__ __forceinline__ uint64_t mkd(uint32_t b16, uint32_t off, uint32_t lbo, uint32_t sbo, uint32_t swz = 0) {
    uint64_t d;
    asm("mov.b64 %0, {%1, %2};" : "=l"(d) : "r"(b16 + ((off >> 4) + ((lbo >> 4) << 16))), "r"((sbo >> 4) | (swz << 30)));
    return d;
}
__device__ __forceinline__ void wgmma_fence() { asm volatile("wgmma.fence.sync.aligned;" ::: "memory"); }
__device__ __forceinline__ void wgmma_commit() { asm volatile("wgmma.commit_group.sync.aligned;" ::: "memory"); }
template <int N> __device__ __forceinline__ void wgmma_wait() { asm volatile("wgmma.wait_group.sync.aligned %0;" :: "n"(N) : "memory"); }
__device__ __forceinline__ void fence_async() { asm volatile("fence.proxy.async.shared::cta;" ::: "memory"); }
template <int N> __device__ __forceinline__ void reg_fence(float* d) {
    #pragma unroll
    for (int i = 0; i < N; i++) asm volatile("" : "+f"(d[i]) :: "memory");
}
#define X16(c, d, o) c(d[o]),c(d[o+1]),c(d[o+2]),c(d[o+3]),c(d[o+4]),c(d[o+5]),c(d[o+6]),c(d[o+7]),c(d[o+8]),c(d[o+9]),c(d[o+10]),c(d[o+11]),c(d[o+12]),c(d[o+13]),c(d[o+14]),c(d[o+15])
#define RW(x) "+f"(x)
#define WO(x) "=f"(x)
#define R64(d) X16(RW, d, 0), X16(RW, d, 16), X16(RW, d, 32), X16(RW, d, 48)
#define W64(d) X16(WO, d, 0), X16(WO, d, 16), X16(WO, d, 32), X16(WO, d, 48)
#define R16(d) X16(RW, d, 0)
#define WO16(d) X16(WO, d, 0)
#define L64 "{%0,%1,%2,%3,%4,%5,%6,%7,%8,%9,%10,%11,%12,%13,%14,%15,%16,%17,%18,%19,%20,%21,%22,%23,%24,%25,%26,%27,%28,%29,%30,%31," \
        "%32,%33,%34,%35,%36,%37,%38,%39,%40,%41,%42,%43,%44,%45,%46,%47,%48,%49,%50,%51,%52,%53,%54,%55,%56,%57,%58,%59,%60,%61,%62,%63}"
#define L16 "{%0,%1,%2,%3,%4,%5,%6,%7,%8,%9,%10,%11,%12,%13,%14,%15}"

template <int TA, int TB> __device__ __forceinline__ void ss128(float* d, uint64_t a, uint64_t b) {
    asm volatile("wgmma.mma_async.sync.aligned.m64n128k16.f32.bf16.bf16 " L64 ", %64, %65, 1, 1, 1, %66, %67;\n" : R64(d) : "l"(a), "l"(b), "n"(TA), "n"(TB));
}
template <int TA, int TB> __device__ __forceinline__ void ss128_p(float* d, uint64_t a, uint64_t b, int acc) {
    asm volatile("{\n.reg .pred p;\nsetp.ne.s32 p, %68, 0;\nwgmma.mma_async.sync.aligned.m64n128k16.f32.bf16.bf16 " L64 ", %64, %65, p, 1, 1, %66, %67;\n}\n" : R64(d) : "l"(a), "l"(b), "n"(TA), "n"(TB), "r"(acc));
}
template <int TA, int TB> __device__ __forceinline__ void ss128_z(float* d, uint64_t a, uint64_t b) {
    asm volatile("wgmma.mma_async.sync.aligned.m64n128k16.f32.bf16.bf16 " L64 ", %64, %65, 0, 1, 1, %66, %67;\n" : W64(d) : "l"(a), "l"(b), "n"(TA), "n"(TB));
}
__device__ __forceinline__ void rs32(float* d, uint32_t a0, uint32_t a1, uint32_t a2, uint32_t a3, uint64_t b) {
    asm volatile("wgmma.mma_async.sync.aligned.m64n32k16.f32.bf16.bf16 " L16 ", {%16,%17,%18,%19}, %20, 1, 1, 1, 0;\n"
        : R16(d) : "r"(a0), "r"(a1), "r"(a2), "r"(a3), "l"(b));
}
__device__ __forceinline__ void rs32_z(float* d, uint32_t a0, uint32_t a1, uint32_t a2, uint32_t a3, uint64_t b) {
    asm volatile("wgmma.mma_async.sync.aligned.m64n32k16.f32.bf16.bf16 " L16 ", {%16,%17,%18,%19}, %20, 0, 1, 1, 0;\n"
        : WO16(d) : "r"(a0), "r"(a1), "r"(a2), "r"(a3), "l"(b));
}
__device__ __forceinline__ void stsm_x4(uint32_t addr, uint32_t r0, uint32_t r1, uint32_t r2, uint32_t r3) {
    asm volatile("stmatrix.sync.aligned.m8n8.x4.shared.b16 [%0], {%1, %2, %3, %4};" :: "r"(addr), "r"(r0), "r"(r1), "r"(r2), "r"(r3) : "memory");
}
__device__ __forceinline__ uint32_t lds32(uint32_t a) { uint32_t v; asm volatile("ld.shared.u32 %0, [%1];" : "=r"(v) : "r"(a) : "memory"); return v; }
__device__ __forceinline__ uint2 lds64(uint32_t a) { uint2 v; asm volatile("ld.shared.v2.u32 {%0, %1}, [%2];" : "=r"(v.x), "=r"(v.y) : "r"(a) : "memory"); return v; }
__device__ __forceinline__ uint4 lds128(uint32_t a) { uint4 v; asm volatile("ld.shared.v4.u32 {%0, %1, %2, %3}, [%4];" : "=r"(v.x), "=r"(v.y), "=r"(v.z), "=r"(v.w) : "r"(a) : "memory"); return v; }
__device__ __forceinline__ void sts32(uint32_t a, uint32_t x) { asm volatile("st.shared.u32 [%0], %1;" :: "r"(a), "r"(x) : "memory"); }
__device__ __forceinline__ void sts128(uint32_t a, uint32_t x, uint32_t y, uint32_t z, uint32_t w) {
    asm volatile("st.shared.v4.u32 [%0], {%1, %2, %3, %4};" :: "r"(a), "r"(x), "r"(y), "r"(z), "r"(w) : "memory");
}
__device__ __forceinline__ float bflo(uint32_t v) { return __uint_as_float(v << 16); }
__device__ __forceinline__ float bfhi(uint32_t v) { return __uint_as_float(v & 0xffff0000u); }
__device__ __forceinline__ uint32_t hmul2bf(uint32_t a, uint32_t b) { uint32_t r; asm("mul.rn.bf16x2 %0, %1, %2;" : "=r"(r) : "r"(a), "r"(b)); return r; }
__device__ __forceinline__ void mbar_init(uint32_t a, uint32_t c) { asm volatile("mbarrier.init.shared.b64 [%0], %1;" :: "r"(a), "r"(c)); }
__device__ __forceinline__ void mbar_wait(uint32_t a, uint32_t ph) {
    asm volatile("{\n.reg .pred p;\n.reg .u32 n;\nmov.u32 n, 0;\nWAIT_LOOP:\nmbarrier.try_wait.parity.shared.b64 p, [%0], %1;\n@p bra DONE;\nadd.u32 n, n, 1;\nsetp.lt.u32 p, n, 4000000;\n@p bra WAIT_LOOP;\nDONE:\n}" :: "r"(a), "r"(ph) : "memory");
}
__device__ __forceinline__ void mbar_wait_n(uint32_t a, uint32_t ph, uint32_t& n) {
    asm volatile("{\n.reg .pred p;\nWAIT_LOOP:\nmbarrier.try_wait.parity.shared.b64 p, [%1], %2;\n@p bra DONE;\nadd.u32 %0, %0, 1;\nsetp.lt.u32 p, %0, 4000000;\n@p bra WAIT_LOOP;\nDONE:\n}" : "+r"(n) : "r"(a), "r"(ph) : "memory");
}
__device__ __forceinline__ void mbar_expect_tx(uint32_t a, uint32_t bytes) { asm volatile("mbarrier.arrive.expect_tx.shared.b64 _, [%0], %1;" :: "r"(a), "r"(bytes) : "memory"); }
__device__ __forceinline__ void mbar_arrive(uint32_t a) { asm volatile("mbarrier.arrive.shared.b64 _, [%0];" :: "r"(a) : "memory"); }
__device__ __forceinline__ void mbar_arrive2(uint32_t a) { asm volatile("mbarrier.arrive.shared.b64 _, [%0], 2;" :: "r"(a) : "memory"); }
__device__ __forceinline__ void tma_load_2d(uint32_t dst, const CUtensorMap* map, int c0, int c1, uint32_t bar) {
    asm volatile("cp.async.bulk.tensor.2d.shared::cluster.global.mbarrier::complete_tx::bytes [%0], [%1, {%3, %4}], [%2];"
        :: "r"(dst), "l"(map), "r"(bar), "r"(c0), "r"(c1) : "memory");
}
__device__ __forceinline__ void tma_load_3d(uint32_t dst, const CUtensorMap* map, int c0, int c1, int c2, uint32_t bar) {
    asm volatile("cp.async.bulk.tensor.3d.shared::cluster.global.mbarrier::complete_tx::bytes [%0], [%1, {%3, %4, %5}], [%2];"
        :: "r"(dst), "l"(map), "r"(bar), "r"(c0), "r"(c1), "r"(c2) : "memory");
}
__device__ __forceinline__ void tma_load_4d(uint32_t dst, const CUtensorMap* map, int c0, int c3, uint32_t bar) {
    asm volatile("cp.async.bulk.tensor.4d.shared::cluster.global.mbarrier::complete_tx::bytes [%0], [%1, {%3, %5, %5, %4}], [%2];"
        :: "r"(dst), "l"(map), "r"(bar), "r"(c0), "r"(c3), "r"(0) : "memory");
}
__device__ __forceinline__ void tma_load_5d(uint32_t dst, const CUtensorMap* map, int c0, int c4, uint32_t bar) {
    asm volatile("cp.async.bulk.tensor.5d.shared::cluster.global.mbarrier::complete_tx::bytes [%0], [%1, {%3, %5, %5, %5, %4}], [%2];"
        :: "r"(dst), "l"(map), "r"(bar), "r"(c0), "r"(c4), "r"(0) : "memory");
}
__device__ __forceinline__ void bulk_load(uint32_t dst, const void* src, uint32_t bytes, uint32_t bar) {
    asm volatile("cp.async.bulk.shared::cluster.global.mbarrier::complete_tx::bytes [%0], [%1], %2, [%3];" :: "r"(dst), "l"(src), "r"(bytes), "r"(bar) : "memory");
}
__device__ __forceinline__ void wait_counter(const unsigned int* p, unsigned int target) {
    unsigned int cur; int spins = 0;
    #pragma unroll 1
    do {
        asm volatile("ld.relaxed.gpu.global.u32 %0, [%1];" : "=r"(cur) : "l"(p) : "memory");
        if ((int)(cur - target) >= 0) break;
        __nanosleep(40);
    } while (++spins < (1 << 22));
}
__device__ __forceinline__ void red_release(unsigned int* p) { asm volatile("red.release.gpu.global.add.u32 [%0], 1;" :: "l"(p) : "memory"); }
__device__ __forceinline__ uint32_t clk32() { uint32_t c; asm volatile("mov.u32 %0, %%clock;" : "=r"(c)); return c; }
__device__ __forceinline__ bool elect_one() {
    uint32_t r;
    asm volatile("{\n.reg .pred p;\nelect.sync _|p, 0xffffffff;\nselp.u32 %0, 1, 0, p;\n}" : "=r"(r));
    return r != 0;
}
__device__ __forceinline__ int tid128() { int t; asm volatile("mov.u32 %0, %%tid.x;" : "=r"(t)); return t & 127; }
typedef __nv_bfloat162 bf2;
__device__ __forceinline__ bf2 asbf2(uint32_t v) { return *reinterpret_cast<bf2*>(&v); }
__device__ __forceinline__ uint32_t asu32(bf2 v) { return *reinterpret_cast<uint32_t*>(&v); }
template <int M> struct W16 { static constexpr uint32_t c = ct::bf16bits(ct::cos2048(128 * M)) * 0x10001u, s = ct::bf16bits(-ct::sin2048(128 * M)) * 0x10001u; };
__device__ __forceinline__ void pin(bf2& v) { uint32_t u = asu32(v); asm volatile("" : "+r"(u) :: "memory"); v = asbf2(u); }
__device__ __forceinline__ bf2 neg2(bf2 v) { return asbf2(asu32(v) ^ 0x80008000u); }
__device__ __forceinline__ void cmul2(bf2& r, bf2& i, bf2 wr, bf2 wi) {
    const bf2 a = r, b = i;
    r = __hfma2(a, wr, __hmul2(b, neg2(wi))); i = __hfma2(b, wr, __hmul2(a, wi));
}
__device__ __forceinline__ void bfly4(bf2* r, bf2* i, int o, int s) {
    const bf2 ar = __hadd2(r[o], r[o + 2 * s]), ai = __hadd2(i[o], i[o + 2 * s]), br = __hsub2(r[o], r[o + 2 * s]), bi = __hsub2(i[o], i[o + 2 * s]);
    const bf2 cr = __hadd2(r[o + s], r[o + 3 * s]), ci = __hadd2(i[o + s], i[o + 3 * s]), dr = __hsub2(r[o + s], r[o + 3 * s]), di = __hsub2(i[o + s], i[o + 3 * s]);
    r[o] = __hadd2(ar, cr); i[o] = __hadd2(ai, ci); r[o + 2 * s] = __hsub2(ar, cr); i[o + 2 * s] = __hsub2(ai, ci);
    r[o + s] = __hadd2(br, di); i[o + s] = __hsub2(bi, dr); r[o + 3 * s] = __hsub2(br, di); i[o + 3 * s] = __hadd2(bi, dr);
}
template <int M> __device__ __forceinline__ void tw16(bf2& r, bf2& i) {
    if (M == 4) { const bf2 a = r; r = i; i = neg2(a); }
    else cmul2(r, i, asbf2(W16<M>::c), asbf2(W16<M>::s));
}
__device__ __forceinline__ void tw16_all(bf2* r, bf2* i) {
    tw16<1>(r[5], i[5]); tw16<2>(r[6], i[6]); tw16<3>(r[7], i[7]); tw16<2>(r[9], i[9]); tw16<4>(r[10], i[10]); tw16<6>(r[11], i[11]);
    tw16<3>(r[13], i[13]); tw16<6>(r[14], i[14]); tw16<9>(r[15], i[15]);
}

__device__ __forceinline__ void dft16(bf2* r, bf2* i) {
    #pragma unroll
    for (int r0 = 0; r0 < 4; r0++) bfly4(r, i, r0, 4);
    tw16_all(r, i);
    #pragma unroll
    for (int k1 = 0; k1 < 4; k1++) bfly4(r, i, 4 * k1, 1);
}
__device__ __forceinline__ void idft16(bf2* r, bf2* i) {
    #pragma unroll
    for (int k1 = 0; k1 < 4; k1++) bfly4(i, r, 4 * k1, 1);
    tw16_all(i, r);
    #pragma unroll
    for (int r0 = 0; r0 < 4; r0++) bfly4(i, r, r0, 4);
}

#define DBAR 1
#define FBAR 2
#define TBAR 4
#define HBAR 6
#define GBAR 10
#define LBAR 11
#define KBAR 15
#define FULL(s) (bars + 8 * (s))
#define EMPTY(s) (bars + 8 * (RING + (s)))
#define XB (bars + 64)
#define X1B(h) (bars + 72 + 8 * (h))
#define ZOK (bars + 88)
#define EPB (bars + 96)
#define R0F (bars + 104)
#define HOK(i) (bars + 112 + 8 * (i))
#define WQ(i) (bars + 144 + 8 * (i))
#define EPO_OFF (BAR_OFF + 176)
#define ROLE_OFF (BAR_OFF + 180)
#define SACT_OFF (BAR_OFF + 184)
#define PT_OFF (R2 + 26624)
#define LAM_OFF (R2 + 27648)
#define WBUF(i) ((i) == 1 ? R1 : ((i) == 2 ? R1 + 16384 : R2 + 10240))
#define PC1 448
#define PC1M 256
#define P1END 8500
#define PC2 88
#define PCR 96
#define PCH 160
#define PCL 100
#define PCW 200
#define PCZ 500
#define TXT 1400
#define TTAB 8500
#define PFW 5000
#define PFB 9000
#define PFC 12000
#define PFCS 2000
__device__ __forceinline__ void delay(int cycles) { const uint32_t c = clk32(); while ((int)(clk32() - c) < cycles) { } }
__device__ __forceinline__ void pace(uint32_t& t, int cycles) { while ((int)(clk32() - t) < 0) { } t += cycles; }
__device__ __forceinline__ void pf_line(const void* p) { asm volatile("prefetch.global.L2 [%0];" :: "l"(p)); }

__device__ __forceinline__ float2 cis(int m) { return __ldg(reinterpret_cast<const float2*>(g_img.cs[m & 15][(m >> 4) & 127])); }
__device__ __forceinline__ void gen_dft(uint32_t dst, int j, float2 w, float2 b, int b0, int b1, float c0) {
    const float c2 = 2.f * w.x;
    float2 a = cmul(b, w);
    float2 z0 = b0 ? b : make_float2(c0, (j & 1) ? -c0 : c0);
    dst += j * 128;
    #pragma unroll 1
    for (int blk = b0; blk < b1; blk++) {
        float2 v[9];
        v[0] = b;
        v[1] = make_float2(fmaf(c2, b.x, -a.x), fmaf(c2, b.y, -a.y));
        #pragma unroll
        for (int k = 2; k < 9; k++) v[k] = make_float2(fmaf(c2, v[k - 1].x, -v[k - 2].x), fmaf(c2, v[k - 1].y, -v[k - 2].y));
        const uint32_t p = dst + (blk >> 2) * 16384, c = (2 * (blk & 3)) ^ (j & 7);
        sts128(p + c * 16, pack2(z0.x, v[1].x), pack2(v[2].x, v[3].x), pack2(v[4].x, v[5].x), pack2(v[6].x, v[7].x));
        sts128(p + (c ^ 1) * 16, pack2(z0.y, v[1].y), pack2(v[2].y, v[3].y), pack2(v[4].y, v[5].y), pack2(v[6].y, v[7].y));
        a = v[7]; b = v[8]; z0 = b;
    }
}

__device__ __forceinline__ void fft_p1(uint32_t sbase, uint32_t bars, int tile, int r, int db, uint32_t t_end) {
    constexpr uint32_t s16 = SBASE / 16;
    float acc[64];
    wgmma_fence();
    ss128_z<1, 1>(acc, mkd(s16 + tile * 1024, R1, 16384, 1024, 1), mkd(s16, R0, 16384, 1024, 1));
    #pragma unroll
    for (int ks = 1; ks < 8; ks++) ss128<1, 1>(acc, mkd(s16 + tile * 1024, R1 + ks * 2048, 16384, 1024, 1), mkd(s16, R0 + ks * 2048, 16384, 1024, 1));
    wgmma_commit();
    const int tid = tid128();
    float g0 = 0.f;
    uint4* dst = g_X1 + (64 * tile + 2 * (tid >> 2)) * 2048 + (r >> 3) * 1024 + db * 128 + (r & 7) * 16 + (tid & 3);
    wgmma_wait<0>();
    reg_fence<64>(acc);
    uint32_t tp = clk32();
    const int dt = min(max((int)(t_end - tp) >> 3, PC1M), PC1);
    tp += (threadIdx.x >> 5 & 7) * (dt >> 3);
    #pragma unroll
    for (int c = 0; c < 4; c++) {
        const float* u = acc + 4 * (c >> 1) + (c & 1);
        #pragma unroll
        for (int ke = 0; ke < 2; ke++) {
            float v[8];
            #pragma unroll
            for (int z = 0; z < 8; z++) { const int ix = 8 * (z & 3) + 2 * (z >> 2); v[z] = ke ? u[ix] - u[ix + 32] : u[ix] + u[ix + 32]; }
            uint4 o = make_uint4(pack2(v[0], v[1]), pack2(v[2], v[3]), pack2(v[4], v[5]), pack2(v[6], v[7]));
            asm volatile("" : "+r"(o.x), "+r"(o.y), "+r"(o.z), "+r"(o.w) :: "memory");
            pace(tp, dt);
            __stcg(dst + ke * 2048 + 4 * c, o);
            if (c < 2) {
                #pragma unroll
                for (int k = 4 * c + 2 * ke; k < 4 * c + 2 * ke + 2; k++) {
                    const uint4 x = lds128(sbase + R0 + tile * 16384 + tid * 128 + ((k ^ (tid & 7)) << 4)), gv = lds128(sbase + GATE_OFF + tile * 128 + k * 16);
                    const uint32_t p0 = hmul2bf(x.x, gv.x), p1 = hmul2bf(x.y, gv.y), p2 = hmul2bf(x.z, gv.z), p3 = hmul2bf(x.w, gv.w);
                    g0 += ((bflo(p0) + bfhi(p0)) + (bflo(p1) + bfhi(p1))) + ((bflo(p2) + bfhi(p2)) + (bflo(p3) + bfhi(p3)));
                }
            }
            if (c == 1 && ke == 1) {
                __stcg(&g_gp[(16 * r + 2 * db + tile) * 128 + tid], g0);
                __syncwarp();
                if ((tid & 31) == 0) mbar_arrive(R0F);
            }
        }
    }
    bar_arrive_n(GBAR, 288);
}

__device__ __forceinline__ int w_first(int unit, int hb) { const int ka = unit >> 1, ke = unit & 1; return hb ? ((128 - ka) & 127) * 513 + 2 - ke : ka * 513 + ke; }
__device__ __forceinline__ void load_w(const CUtensorMap* wm, uint32_t sbase, int unit, int i) {
    const uint32_t bars = sbase + BAR_OFF;
    mbar_expect_tx(WQ(i), 16384);
    #pragma unroll 1
    for (int a = 0; a < 4; a++) { tma_load_3d(sbase + WBUF(i) + a * 4096, wm + (i & 1), w_first(unit, i >> 1) & ~15, 0, 4 * a, WQ(i)); delay(PCW); }
}
__device__ __forceinline__ uint32_t w_off(int e) { e &= 511; return (e >> 6) * 128 + ((((e >> 3) ^ (e >> 6)) & 7) << 4) + (e & 7) * 2; }
__device__ __forceinline__ void sts16(uint32_t a, uint32_t v) { asm volatile("st.shared.u16 [%0], %1;" :: "r"(a), "h"((unsigned short)v) : "memory"); }
__device__ __forceinline__ void boundary() { while (clk32() == 0) { } asm volatile("" ::: "memory"); }
__device__ __forceinline__ void yield_to_scan(uint32_t sbase) {
    #pragma unroll 1
    for (int n = 0; n < 100000 && lds32(sbase + SACT_OFF); n++) __nanosleep(50);
}
template <int OFF> __device__ __forceinline__ uint32_t lds_w(uint32_t a, uint32_t b) {
    uint32_t l, h;
    asm volatile("ld.shared.u16 %0, [%2 + %4];\nld.shared.u16 %1, [%3 + %4];" : "=r"(l), "=r"(h) : "r"(a), "r"(b), "n"(OFF) : "memory");
    return __byte_perm(l, h, 0x5410);
}
template <int S> __device__ __forceinline__ void load_ws(uint32_t* w, uint32_t a, uint32_t b) {
    if constexpr (S < 16) { w[S] = lds_w<((S >> 2) + 4 * (S & 3)) * 1024>(a, b); load_ws<S + 1>(w, a, b); }
}
template <int I> __device__ __forceinline__ void fetch_w(uint32_t* w, uint32_t sbase, int unit) {
    constexpr int hb = I >> 1;
    const uint32_t bars = sbase + BAR_OFF, buf = sbase + WBUF(I);
    const int tid = tid128(), sh = w_first(unit, hb) & 15;
    const uint32_t pt = lds32(sbase + PT_OFF + 512 * hb + 4 * tid) >> (16 * (I & 1)), sp = lds32(sbase + DSK_OFF + 4 * (tid & 31)) >> (16 * (I & 1));
    mbar_wait(WQ(I), 0);
    if ((sh & 1) + 2 * (tid & 7) + 2 <= sh) sts16(buf + (tid >> 3) * 1024 + ((sh & 1) + 2 * (tid & 7)) * 2, pt);
    bar_sync_n(FBAR, 128);
    if (!(unit & 1) && (tid >> 4) == hb) sts16(buf + w_off(sh + 510 * hb) + (tid & 15) * 1024, sp);
    __syncwarp();
    boundary();
    const int pos = 128 * (tid & 3) + 2 * (tid >> 2);
    const bool rot = hb && unit >= 2;
    const uint32_t o0 = buf + w_off(sh + (hb ? 510 - pos : pos)) - (rot ? 1024 : 0), o1 = buf + w_off(sh + (hb ? 446 - pos : pos + 64)) - (rot ? 1024 : 0), oz = rot ? 16384 : 0;
    w[0] = lds_w<0>(o0 + oz, o1 + oz);
    load_ws<1>(w, o0, o1);
}
__device__ __forceinline__ void pin16(bf2* r, bf2* i) {
    #pragma unroll
    for (int k = 0; k < 16; k++) { pin(r[k]); pin(i[k]); }
}

__device__ __forceinline__ void fft_p2(uint32_t sbase, uint32_t bars, int unit, const __nv_bfloat16* w_r, const __nv_bfloat16* w_i) {
    constexpr uint32_t s16 = SBASE / 16;
    const ct::Half* tb = &g_img.h[unit & 1];
    uint32_t P[16][4];
    uint32_t wr[16], wi[16];
    uint4 t;
    {
        const int tid = tid128();
        uint32_t sp = 0, pt[2] = {0, 0};
        t = __ldg(reinterpret_cast<const uint4*>(tb->tw[0][tid]));
        if (tid < 32 && !(unit & 1)) {
            const int k1 = ((tid & 16) ? (128 - (unit >> 1)) & 127 : unit >> 1) + 128 * (tid & 15), o1 = k1 * 513 + 32 * (tid & 16), o2 = ((2048 - k1) & 2047) * 513 + 32 * (tid & 16);
            sp = pack2(0.5f * (__bfloat162float(w_r[o1]) + __bfloat162float(w_r[o2])), 0.5f * (__bfloat162float(w_i[o1]) - __bfloat162float(w_i[o2])));
        }
        #pragma unroll
        for (int hb = 0; hb < 2; hb++) {
            const int e0 = w_first(unit, hb), z = (e0 & 1) + 2 * (tid & 7), o = (tid >> 3) * 65664 + (e0 & ~15) + 512 + z;
            if (z + 2 <= (e0 & 15)) pt[hb] = reinterpret_cast<const unsigned short*>(w_r)[o] | ((uint32_t)reinterpret_cast<const unsigned short*>(w_i)[o] << 16);
        }
        sts32(sbase + PT_OFF + 4 * tid, pt[0]); sts32(sbase + PT_OFF + 512 + 4 * tid, pt[1]);
        mbar_wait(X1B(0), 0);
        if (tid < 32) sts32(sbase + DSK_OFF + 4 * tid, sp);
        if (unit >= 128) {
            mbar_wait(X1B(1), 0);
            #pragma unroll 1
            for (int i = 0; i < 16; i++) {
                const float2 w = cis(-64 * ((i & 8) + (tid >> 4)));
                const uint32_t a = sbase + R1 + (i * 128 + tid) * 16;
                const uint2 v = lds64(a + 8);
                sts128(a, pack2(bflo(v.x) * w.x, bfhi(v.x) * w.x), pack2(bflo(v.y) * w.x, bfhi(v.y) * w.x), pack2(bflo(v.x) * w.y, bfhi(v.x) * w.y), pack2(bflo(v.y) * w.y, bfhi(v.y) * w.y));
            }
            fence_async();
            bar_sync_n(FBAR, 128);
        }
        #pragma unroll
        for (int h = 0; h < 2; h++) {
            float acc[64];
            if (h) mbar_wait(X1B(1), 0);
            wgmma_fence();
            ss128_z<1, 0>(acc, mkd(s16, R2, 1024, 128), mkd(s16, R1 + h * 16384, 2048, 128));
            #pragma unroll
            for (int s = 1; s < 4; s++) ss128<1, 0>(acc, mkd(s16, R2 + s * 2048, 1024, 128), mkd(s16, R1 + h * 16384 + s * 4096, 2048, 128));
            wgmma_commit();
            if (h == 1) {
                fetch_w<0>(wr, sbase, unit);
                #pragma unroll
                for (int s = 0; s < 16; s++) asm volatile("" : "+r"(wr[s]) :: "memory");
                if (unit > 999) sts32(sbase + SACT_OFF + 4, wr[15]);
            }
            wgmma_wait<0>();
            reg_fence<64>(acc);
            bar_arrive_n(LBAR + h, 160);
            bf2 f[32];
            #pragma unroll
            for (int z = 0; z < 32; z++) { uint32_t u = pack2(acc[2 * z], acc[2 * z + 1]); asm volatile("" : "+r"(u) :: "memory"); f[z] = asbf2(u); }
            boundary();
            float d[2][16];
            #pragma unroll
            for (int pr = 0; pr < 5; pr++) {
                if (pr == 2) boundary();
                if (pr < 4) {
                    bf2* a = f + 8 * pr;
                    #pragma unroll
                    for (int z = 0; z < 8; z++) pin(a[z]);
                    #pragma unroll
                    for (int z = 0; z < 4; z++) cmul2(a[2 * z], a[2 * z + 1], asbf2((z & 1) ? t.z : t.x), asbf2((z & 1) ? t.w : t.y));
                    wgmma_fence();
                    rs32_z(d[pr & 1], asu32(a[0]), asu32(a[4]), asu32(a[2]), asu32(a[6]), mkd(s16, B16F_OFF, 128, 512));
                    rs32(d[pr & 1], asu32(a[1]), asu32(a[5]), asu32(a[3]), asu32(a[7]), mkd(s16, B16F_OFF + 256, 128, 512));
                    wgmma_commit();
                }
                if (pr > 0) {
                    if (pr < 4) wgmma_wait<1>(); else wgmma_wait<0>();
                    reg_fence<16>(d[(pr - 1) & 1]);
                    #pragma unroll
                    for (int z = 0; z < 8; z++) {
                        uint32_t& p = P[8 * h + 2 * pr - 2 + (z & 1)][z >> 1];
                        p = pack2(d[(pr - 1) & 1][2 * z], d[(pr - 1) & 1][2 * z + 1]);
                        asm volatile("" : "+r"(p) :: "memory");
                    }
                }
            }
        }
    }
    {
        bf2 vr[2][16], vi[2][16];
        #pragma unroll
        for (int r = 0; r < 16; r++) { vr[0][r] = asbf2(P[r][0]); vr[1][r] = asbf2(P[r][1]); vi[0][r] = asbf2(P[r][2]); vi[1][r] = asbf2(P[r][3]); }
        fetch_w<1>(wi, sbase, unit);
        pin16(vr[0], vi[0]);
        dft16(vr[0], vi[0]);
        #pragma unroll
        for (int s = 0; s < 16; s++) cmul2(vr[0][s], vi[0][s], asbf2(wr[s]), asbf2(wi[s]));
        fetch_w<2>(wr, sbase, unit);
        pin16(vr[1], vi[1]);
        dft16(vr[1], vi[1]);
        fetch_w<3>(wi, sbase, unit);
        asm volatile("ld.global.nc.v4.u32 {%0, %1, %2, %3}, [%4];" : "=r"(t.x), "=r"(t.y), "=r"(t.z), "=r"(t.w) : "l"(tb->tw[1][tid128()]) : "memory");
        pin16(vr[0], vi[0]);
        idft16(vr[0], vi[0]);
        #pragma unroll
        for (int s = 0; s < 16; s++) cmul2(vr[1][s], vi[1][s], asbf2(wr[s]), asbf2(wi[s]));
        bar_sync_n(FBAR, 128);
        idft16(vr[1], vi[1]);
        #pragma unroll
        for (int r = 0; r < 16; r++) { P[r][0] = asu32(vr[0][r]); P[r][1] = asu32(vr[1][r]); P[r][2] = asu32(vi[0][r]); P[r][3] = asu32(vi[1][r]); }
    }
    {
        const int tid = tid128(), ka = unit >> 1;
        const uint32_t zero = unit >> 8;
        const uint32_t sa = sbase + R1 + ((tid >> 3) & 1) * 1024 + (2 * (tid >> 5) + ((tid >> 4) & 1)) * 128 + (tid & 7) * 16;
        uint8_t* dst = reinterpret_cast<uint8_t*>(g_X2) + (2 * (tid >> 5)) * X2_IMG + (unit & 1) * (X2_IMG / 2)
                     + (16 * (ka >> 3) + 8 * ((tid >> 4) & 1) + (ka & 7)) * 128 + ((((tid >> 1) & 7) ^ (ka & 7)) << 4) + (tid & 1) * 8;
        uint32_t o[32], late = ~0u << 5;
        #pragma unroll
        for (int h = 0; h < 2; h++) {
            float d[2][16];
            #pragma unroll
            for (int pr = 0; pr < 5; pr++) {
                if (!(pr & 1)) boundary();
                const uint32_t busy = h ? lds32(sbase + SACT_OFF) : 0;
                if (pr < 4) {
                    uint32_t a[8];
                    #pragma unroll
                    for (int z = 0; z < 8; z++) asm volatile("xor.b32 %0, %1, %2;" : "=r"(a[z]) : "r"(P[8 * h + 2 * pr + (z >> 2)][z & 3]), "r"(zero) : "memory");
                    wgmma_fence();
                    rs32_z(d[pr & 1], a[0], a[4], a[1], a[5], mkd(s16, R2 + 8192, 128, 512));
                    rs32(d[pr & 1], a[2], a[6], a[3], a[7], mkd(s16, R2 + 8192 + 256, 128, 512));
                    wgmma_commit();
                }
                if (h) {
                    if (busy) late |= 1u << pr;
                    #pragma unroll
                    for (int z = 2 * pr; z < 2 * pr + 2; z++) if (!busy) __stcg(reinterpret_cast<uint2*>(dst + (8 * (z >> 1) + (z & 1)) * X2_IMG), make_uint2(o[2 * z], o[2 * z + 1]));
                }
                if (pr > 0) {
                    if (pr < 4) wgmma_wait<1>(); else wgmma_wait<0>();
                    reg_fence<16>(d[(pr - 1) & 1]);
                    #pragma unroll
                    for (int rl = 0; rl < 2; rl++) {
                        const float* a = d[(pr - 1) & 1] + 2 * rl;
                        bf2 r0 = asbf2(pack2(a[0], a[1])), r1 = asbf2(pack2(a[4], a[5])), i0 = asbf2(pack2(a[8], a[9])), i1 = asbf2(pack2(a[12], a[13]));
                        cmul2(r0, i0, asbf2(t.x), asbf2(t.y)); cmul2(r1, i1, asbf2(t.z), asbf2(t.w));
                        stsm_x4(sa + (8 * h + 2 * pr - 2 + rl) * 2048, asu32(r0), asu32(r1), asu32(i0), asu32(i1));
                    }
                }
            }
            fence_async();
            bar_sync_n(FBAR, 128);
            boundary();
            float acc[64];
            wgmma_fence();
            ss128_z<0, 1>(acc, mkd(s16, R2, 128, 1024), mkd(s16, R1 + h * 16384, 128, 1024));
            #pragma unroll
            for (int s = 1; s < 4; s++) ss128<0, 1>(acc, mkd(s16, R2 + s * 256, 128, 1024), mkd(s16, R1 + h * 16384 + s * 256, 128, 1024));
            wgmma_commit();
            if (h) yield_to_scan(sbase);
            uint32_t tp = clk32();
            if (h) {
                #pragma unroll
                for (int z = 0; z < 16; z += 2)
                    if ((late >> (z / 2)) & 1) {
                        pace(tp, 2 * PC2);
                        __stcg(reinterpret_cast<uint2*>(dst + (4 * z) * X2_IMG), make_uint2(o[2 * z], o[2 * z + 1]));
                        __stcg(reinterpret_cast<uint2*>(dst + (4 * z + 1) * X2_IMG), make_uint2(o[2 * z + 2], o[2 * z + 3]));
                    }
            }
            wgmma_wait<0>();
            reg_fence<64>(acc);
            #pragma unroll
            for (int z = 0; z < 16; z++) { const float* a = acc + 8 * (z >> 1) + 2 * (z & 1); o[2 * z] = pack2(a[0], a[1]); o[2 * z + 1] = pack2(a[4], a[5]); asm volatile("" : "+r"(o[2 * z]), "+r"(o[2 * z + 1]) :: "memory"); }
            if (h) {
                yield_to_scan(sbase);
                tp = clk32() + (tid >> 5) * (PC2 / 2);
                #pragma unroll
                for (int z = 0; z < 16; z++) { if (!(z & 1)) pace(tp, 2 * PC2); __stcg(reinterpret_cast<uint2*>(dst + (64 + 8 * (z >> 1) + (z & 1)) * X2_IMG), make_uint2(o[2 * z], o[2 * z + 1])); }
            }
        }
    }
}

struct Maps { CUtensorMap BB, X, Xr, Cre, Cim, W[2]; };

template <int S> __device__ __forceinline__ void release(uint32_t rel, uint32_t bars) {
    mbar_arrive(EMPTY(S));
    asm volatile("mbarrier.arrive.shared::cluster.b64 _, [%0 + %1];" :: "r"(rel), "n"(8 * (RING + S)) : "memory");
}
__device__ __forceinline__ int peer_role(uint32_t a) { int v; asm volatile("ld.shared::cluster.u32 %0, [%1];" : "=r"(v) : "r"(a ^ (1u << 24)) : "memory"); return v; }
__device__ __forceinline__ void tma_load_3d_mc(uint32_t dst, const CUtensorMap* map, int c0, int c1, int c2, uint32_t bar) {
    asm volatile("cp.async.bulk.tensor.3d.shared::cluster.global.mbarrier::complete_tx::bytes.multicast::cluster [%0], [%1, {%3, %4, %5}], [%2], %6;"
        :: "r"(dst), "l"(map), "r"(bar), "r"(c0), "r"(c1), "r"(c2), "h"((unsigned short)3) : "memory");
}
__device__ __forceinline__ void bulk_load_mc(uint32_t dst, const void* src, uint32_t bytes, uint32_t bar) {
    asm volatile("cp.async.bulk.shared::cluster.global.mbarrier::complete_tx::bytes.multicast::cluster [%0], [%1], %2, [%3], %4;"
        :: "r"(dst), "l"(src), "r"(bytes), "r"(bar), "h"((unsigned short)3) : "memory");
}
template <int TA> __device__ __forceinline__ void mma_round(float* acc, uint32_t bars, uint32_t a16, uint32_t ph, bool lead, int accum, int it, uint32_t& nw, uint32_t peer, int pp, bool lag = false) {
    #pragma unroll
    for (int s = 0; s < RING; s++) {
        if (TA && (s == 1 || s == 2) && lag) bar_sync_n(TBAR + s - 1, 256);
        mbar_wait_n(FULL(s), ph, nw);
        if (!TA || accum < 7 || (s == 0 && !lag)) bar_sync_n(pp, 256);
        wgmma_fence();
        #pragma unroll
        for (int k = 0; k < 4; k++) {
            const uint64_t da = TA ? mkd(a16, s * STGB + k * 256, 128, 1024) : mkd(a16, s * STGB + k * 32, 16, 1024, 1);
            const uint64_t db = mkd(SBASE / 16, s * STGB + 16384 + k * 32, 16, 1024, 1);
            if (k == 0 && s == 0) ss128_p<TA, 0>(acc, da, db, accum); else ss128<TA, 0>(acc, da, db);
        }
        wgmma_commit();
        if (!TA || accum < 7) bar_arrive_n(14 - pp, 256);
        wgmma_wait<1>();
        if (lead && (s > 0 ? (!TA || accum < 7) : accum != 0)) { if (s == 0) release<3>(peer, bars); if (s == 1) release<0>(peer, bars); if (s == 2) release<1>(peer, bars); if (s == 3) release<2>(peer, bars); }
    }
}
__device__ __forceinline__ void gemm_main(float* A, uint32_t sbase, int wg, int warp, int lane, int cb, int tc, int swp) {
    const uint32_t bars = sbase + BAR_OFF;
    const bool lead = tid128() == 0;
    const uint32_t a16 = SBASE / 16 + wg * 512;
    uint32_t nw = 0;
    uint32_t peer = bars ^ ((uint32_t)(lane + 1) << 24);
    asm volatile("" : "+r"(peer));
    asm volatile("barrier.cluster.wait.acquire.aligned;" ::: "memory");
    if (wg) bar_arrive_n(0, 256);
    uint32_t a = sbase + R0 + (((lane >> 3) & 1) ^ swp) * 16384 + (lane >> 4) * 1024 + (wg * 32 + warp * 8 + (lane & 7)) * 16;
    uint32_t pa = sbase + LAM_OFF + (wg * 32 + warp * 8 + (lane >> 2)) * 16;
    unsigned long long* ag = &g_agg[tc * P_DIM + cb * 128 + wg * 32 + warp * 8 + (lane >> 2)];
    asm volatile("" : "+r"(a), "+r"(pa), "+l"(ag));
    #pragma unroll 1
    for (int half = 0; half < 2; half++) {
        uint2 p0;
        uint4 p1;
        uint32_t par;
        #pragma unroll 1
        for (int rd = 0; rd < 4; rd++) {
            if (rd == 3) { mbar_wait_n(EPB, 0, nw); p0 = lds64(pa); p1 = lds128(pa + 2048); par = lds32(sbase + EPO_OFF); }
            mma_round<0>(A, bars, a16, rd & 1, lead, rd, 16 * half + 4 * rd, nw, peer, 14 * wg);
        }
        mbar_wait_n(R0F, half, nw);
        const float2 lam = make_float2(__uint_as_float(p0.x), __uint_as_float(p0.y));
        const float2 l16 = make_float2(__uint_as_float(p1.x), __uint_as_float(p1.y)), l32 = make_float2(__uint_as_float(p1.z), __uint_as_float(p1.w)), l64 = cmul(l32, l32);
        wgmma_wait<0>();
        reg_fence<64>(A);
        if (lead) release<RING - 1>(peer, bars);
        #pragma unroll
        for (int r = 1; r < 16; r++) {
            #pragma unroll
            for (int c = 0; c < 2; c++) {
                const float2 v = cfma(lam, make_float2(A[4 * r - 4 + c], A[4 * r - 2 + c]), make_float2(A[4 * r + c], A[4 * r + 2 + c]));
                A[4 * r + c] = v.x; A[4 * r + 2 + c] = v.y;
            }
            if ((r & 1) && r < 12) { const float* u = A + 4 * r - 4; stsm_x4(a + (r >> 1) * 2048, pack2(u[0], u[1]), pack2(u[2], u[3]), pack2(u[4], u[5]), pack2(u[6], u[7])); }
        }
        {
            float2 e = cfma(l16, make_float2(A[60], A[62]), make_float2(A[61], A[63]));
            float2 o = make_float2(__shfl_xor_sync(0xffffffffu, e.x, 1), __shfl_xor_sync(0xffffffffu, e.y, 1));
            stsm_x4(a + 6 * 2048, pack2(A[48], A[49]), pack2(A[50], A[51]), pack2(A[52], A[53]), pack2(A[54], A[55]));
            e = cfma(l32, o, e);
            o = make_float2(__shfl_xor_sync(0xffffffffu, e.x, 2), __shfl_xor_sync(0xffffffffu, e.y, 2));
            stsm_x4(a + 7 * 2048, pack2(A[56], A[57]), pack2(A[58], A[59]), pack2(A[60], A[61]), pack2(A[62], A[63]));
            e = cfma(l64, o, e);
            if ((lane & 3) == 3)
                asm volatile("st.relaxed.gpu.global.v2.u32 [%0], {%1, %2};" :: "l"(ag),
                             "r"((__float_as_uint(swp ? e.y : e.x) & ~1u) | (par & 1u)), "r"((__float_as_uint(swp ? e.x : e.y) & ~1u) | (par & 1u)) : "memory");
        }
        pa += 1024; ag += 64;
        bar_arrive_n(DBAR, 384);
        if (half) bar_sync_n(KBAR, 384);
    }
    #pragma unroll 1
    for (int rd = 0; rd < 8; rd++) mma_round<1>(A, bars, a16, rd & 1, lead, rd, 32 + 4 * rd, nw, peer, 14 * wg, rd * wg == 7);
}

__device__ __forceinline__ const CUtensorMap* keep(const CUtensorMap* p) { return reinterpret_cast<const CUtensorMap*>(__shfl_sync(0xffffffffu, reinterpret_cast<unsigned long long>(p), 0)); }
__device__ __forceinline__ void produce(const Maps& mp, uint32_t sbase, int RK, int cb, int tc, int db, int rc) {
    const uint32_t bars = sbase + BAR_OFF;
    const CUtensorMap *mb = keep(&mp.BB), *mx = keep(&mp.X), *cr = keep(&mp.Cre), *ci = keep(&mp.Cim);
    if (!elect_one()) return;
    uint32_t nw = 0;
    int kc = 256, row = cb * 16;
    const int xj = tc * 8, xr = RK * 8;
    #pragma unroll 1
    for (int rd = 1; rd < 8; rd++) {
        #pragma unroll
        for (int s = 0; s < RING; s++) {
            mbar_wait_n(EMPTY(s), (rd - 1) & 1, nw);
            mbar_expect_tx(FULL(s), STGB);
            tma_load_3d_mc(sbase + s * STGB + 16384 + RK * 8192, mx, kc, xj, xr, FULL(s));
            tma_load_4d(sbase + s * STGB, mb, kc, row, FULL(s));
            asm volatile("add.s32 %0, %0, 64;" : "+r"(kc));
        }
        if (rd == 3) { kc = 0; row += 8; }
    }
    const uint8_t* hs = reinterpret_cast<const uint8_t*>(g_h) + rc * 32 * 16384 + RK * 8192;
    const int d0 = db * 4, d1 = db * 4 + 32;
    #pragma unroll 1
    for (int rd = 8; rd < 16; rd++) {
        const CUtensorMap* cm = (rd & 2) ? ci : cr;
        kc = (rd & 1) * 512 + (rd & 4) * 16;
        #pragma unroll
        for (int s = 0; s < RING; s++) {
            mbar_wait_n(EMPTY(s), (rd - 1) & 1, nw);
            mbar_expect_tx(FULL(s), STGB);
            if (s) bulk_load_mc(sbase + s * STGB + RK * 8192, hs, 8192, FULL(s));
            tma_load_5d(sbase + s * STGB + 16384, cm, kc, d0, FULL(s));
            tma_load_5d(sbase + s * STGB + 24576, cm, kc, d1, FULL(s));
            if (s == 0) { mbar_wait_n(HOK((rd >> 1) & 3), 0, nw); }
            if (!s) bulk_load_mc(sbase + s * STGB + RK * 8192, hs, 8192, FULL(s));
            asm volatile("add.s32 %0, %0, 128;" : "+r"(kc));
            asm volatile("add.s64 %0, %0, 16384;" : "+l"(hs));
        }
    }
    sts32(sbase + SACT_OFF + 4, 1u);
}

template <bool full> __global__ void __cluster_dims__(2, 1, 1) __launch_bounds__(640, 1)
fused_kernel(const __nv_bfloat16* __restrict__ x, const __nv_bfloat16* __restrict__ Bre, const __nv_bfloat16* __restrict__ Bim, int swp,
             const __nv_bfloat16* __restrict__ w_r, const __nv_bfloat16* __restrict__ w_i,
             const __nv_bfloat16* __restrict__ lam_re, const __nv_bfloat16* __restrict__ lam_im,
             const __nv_bfloat16* __restrict__ log_dt, const __nv_bfloat16* __restrict__ dskip,
             const __nv_bfloat16* __restrict__ gate_w,
             const __nv_bfloat16* __restrict__ Cre, const __nv_bfloat16* __restrict__ Cim, float* __restrict__ out,
             const __grid_constant__ Maps mp) {
    extern __shared__ __align__(1024) uint8_t smem[];
    const uint32_t sbase = SBASE + ((blockIdx.x & 1) << 24);
    if (smem_u32(smem) != sbase) __trap();
    const uint32_t bars = sbase + BAR_OFF;
    const int tid = threadIdx.x, lane = tid & 31;
    const int wg = __shfl_sync(0xffffffffu, tid >> 7, 0), warp = __shfl_sync(0xffffffffu, (tid >> 5) & 3, 0);
    if (tid < 96) {
        const int row = tid >> 2, bx = blockIdx.x & 127;
        const __nv_bfloat16* p = tid < 64 ? x : (tid < 80 ? Bre : Bim);
        pf_line(p + (tid < 64 ? bx * 16 + row : (bx >> 4) * 128 + (bx & 15) * 4 + (row & 3)) * 1024 + (tid & 3) * 64);
    }
    if (wg == 4 && warp == 1 && elect_one()) {
        asm volatile("prefetch.tensormap [%0];" :: "l"(&mp.BB) : "memory");
        asm volatile("prefetch.tensormap [%0];" :: "l"(&mp.X) : "memory");
        asm volatile("prefetch.tensormap [%0];" :: "l"(&mp.Xr) : "memory");
        for (int s = 0; s < RING; s++) mbar_init(EMPTY(s), 4);
        for (int i = 0; i < 14; i++) mbar_init(XB + 8 * i, i == 3 ? 129 : (i == 4 ? 2 : (i == 5 ? 8 : 1)));
        sts32(sbase + SACT_OFF, 0u); sts32(sbase + SACT_OFF + 4, 0u);
        asm volatile("fence.mbarrier_init.release.cluster;" ::: "memory");
        fence_async();
    }
    int cta = blockIdx.x;
    {
        unsigned int smid;
        asm volatile("mov.u32 %0, %%smid;" : "=r"(smid));
        if (full) {
            const int t = smid >> 1, u = (t - 32) / 7;
            const int g = t < 32 ? (t & 7) : (t < 60 ? t - 31 - 7 * u : 0), idx = t < 32 ? (t >> 3) : (t < 60 ? 4 + u : t - 58);
            const int lg = (0x73216540 >> (4 * g)) & 7;
            cta = ((t & ~1) == 60 || t > 65 ? 8 + 2 * t : 16 * lg + 2 * idx) + (smid & 1);
        }
    }
    const int cb = 2 * (cta >> 5) + (cta & 1), tc = (cta >> 1) & 15;
    const int db = 2 * ((cta >> 4) & 3) + (cta & 1), rc = 8 * ((cta >> 6) & 1) + ((cta >> 1) & 7);
    const long long t_start = clock64();
    if (cta >= NCTA) __trap();
    if (wg == 4 && warp == 0) {
        const bool one = elect_one();
        if (one) {
            for (int s = 0; s < RING; s++) mbar_init(FULL(s), 1);
            sts32(sbase + ROLE_OFF, cta);
            asm volatile("fence.mbarrier_init.release.cluster;" ::: "memory");
            fence_async();
        }
        __syncwarp();
        bar_arrive_n(0, 640);
        asm volatile("barrier.cluster.arrive.relaxed.aligned;" ::: "memory");
        if (one && cta < 128) {
            #pragma unroll
            for (int s = 0; s < RING; s++) {
                mbar_expect_tx(FULL(s), STGB);
                tma_load_4d(sbase + s * STGB, &mp.BB, s * 64, cb * 16, FULL(s));
                tma_load_3d(sbase + s * STGB + 16384, &mp.X, s * 64, tc * 8, 0, FULL(s));
                tma_load_3d(sbase + s * STGB + 24576, &mp.X, s * 64, tc * 8, 8, FULL(s));
            }
        }
        __syncwarp();
    } else {
        bar_sync_n(0, 640);
        asm volatile("barrier.cluster.arrive.relaxed.aligned;" ::: "memory");
    }
    if (wg >= 2 || cta >= 128) asm volatile("barrier.cluster.wait.acquire.aligned;" ::: "memory");
    if (wg == 4) {
        asm volatile("setmaxnreg.dec.sync.aligned.u32 24;");
        if (warp == 0) {
            const int prole = __shfl_sync(0xffffffffu, peer_role(sbase + ROLE_OFF), 0);
            const uint32_t rk = blockIdx.x & 1;
            if (cta >= 128) bar_arrive_n(DBAR + (prole >> 30), 64);
            const uint8_t* hs = reinterpret_cast<const uint8_t*>(g_h) + rc * 32 * 16384;
            if (cta < 128 && __all_sync(0xffffffffu, prole == (cta ^ 1))) {
                produce(mp, sbase, rk, cb, tc, db, rc);
            } else if (cta < 128) {
                uint32_t nw = 0;
                if (elect_one()) {
                    #pragma unroll 1
                    for (int it = RING; it < 64; it++) {
                        const int s = it % RING;
                        const uint32_t sa = sbase + s * STGB;
                        if (prole >= 128) mbar_arrive2(EMPTY(s));
                        mbar_wait_n(EMPTY(s), ((it / RING) - 1) & 1, nw);
                        mbar_expect_tx(FULL(s), STGB);
                        if (it < 32) {
                            tma_load_4d(sa, &mp.BB, (it & 15) * 64, cb * 16 + (it >> 4) * 8, FULL(s));
                            tma_load_3d(sa + 16384, &mp.X, (it & 15) * 64, tc * 8, 0, FULL(s));
                            tma_load_3d(sa + 24576, &mp.X, (it & 15) * 64, tc * 8, 8, FULL(s));
                        } else {
                            const CUtensorMap* cm = (it & 8) ? &mp.Cim : &mp.Cre;
                            tma_load_5d(sa + 16384, cm, (it & 7) * 128 + (it & 16) * 4, db * 4, FULL(s));
                            tma_load_5d(sa + 24576, cm, (it & 7) * 128 + (it & 16) * 4, db * 4 + 32, FULL(s));
                            mbar_wait_n(HOK((it >> 3) & 3), 0, nw);
                            bulk_load(sa, hs + (it - 32) * 16384, 16384, FULL(s));
                        }
                    }
                }
            } else if (cta >= 128 && prole < 128 && lane == 0) {
                mbar_arrive2(EMPTY(RING - 1));
                #pragma unroll 1
                for (int p = 0; p < 8; p++) mbar_wait(EMPTY(RING - 1), p & 1);
            }
        } else if (warp == 1) {
            if (cta < 130) {
                #pragma unroll 1
                for (int i = lane; i < 128; i += 32) {
                    const int p = (cb & 7) * 128 + i;
                    const float dt = bf16r(expf(__bfloat162float(log_dt[p]))), lr = __bfloat162float(lam_re[p]), li = __bfloat162float(lam_im[p]);
                    const float er = expf(dt * lr), den = lr * lr + li * li;
                    float sn, cs; sincospif(dt * li * 0.31830988618379067154f, &sn, &cs);
                    cs *= er; sn *= er;
                    sts128(sbase + LAM_OFF + i * 16, __float_as_uint(cs), __float_as_uint(swp ? -sn : sn),
                           __float_as_uint(__fdividef((cs - 1.f) * lr + sn * li, den)), __float_as_uint(__fdividef(sn * lr - (cs - 1.f) * li, den)));
                    float2 l = make_float2(cs, swp ? -sn : sn);
                    l = cmul(l, l); l = cmul(l, l); l = cmul(l, l); l = cmul(l, l);
                    const float2 l2 = cmul(l, l);
                    sts128(sbase + LAM_OFF + 2048 + i * 16, __float_as_uint(l.x), __float_as_uint(l.y), __float_as_uint(l2.x), __float_as_uint(l2.y));
                }
                __syncwarp();
                if (lane == 0) mbar_arrive(EPB);
                mbar_wait(EPB, 0);
                const unsigned int epoch = lds32(sbase + EPO_OFF);
                const bool one = elect_one();
                if (one) {
                    while (clock64() - t_start < TTAB) { __nanosleep(100); }
                    mbar_expect_tx(X1B(0), 16384 + 2048 + 10240);
                    bulk_load(sbase + B16F_OFF, g_img.b16f, 2048, X1B(0));
                    bulk_load(sbase + R2, cta < 2 ? g_img.m4re[cta] : g_img.h[cta & 1].m4, 8192, X1B(0));
                    bulk_load(sbase + R2 + 8192, g_img.h[cta & 1].b16i, 2048, X1B(0));
                }
                __syncwarp();
                if (cta < 128) bar_sync_n(GBAR, 288);
                if (one) {
                    if (cta < 128) { red_release(&g_cnt1); }
                    mbar_expect_tx(X1B(1), 16384);
                    wait_counter(&g_cnt1, 128u * epoch);
                    #pragma unroll 1
                    for (int i = 0; i < 4; i++) { bulk_load(sbase + R1 + i * 8192, g_X1 + (cta & 127) * 2048 + i * 512, 8192, X1B(i >> 1)); delay(PCL); }
                }
                #pragma unroll 1
                for (int i = 0; i < 4; i++) {
                    if (one) load_w(mp.W, sbase, cta, i);
                    __syncwarp();
                    if (i != 2) bar_sync_n(LBAR + min(i, 2), 160);
                }
                if (one) {
                    red_release(cta < 128 ? &g_cnt2 : &g_cnt3);
                    if (cta < 128) {
                        const uint8_t* img = reinterpret_cast<const uint8_t*>(g_X2) + (8 * rc + db) * X2_IMG;
                        mbar_expect_tx(ZOK, 32768 - 256);
                        wait_counter(&g_cnt2, 128u * epoch);
                        const int dz = lds32(sbase + SACT_OFF + 4) ? 0 : PCZ;
                        #pragma unroll
                        for (int k = 0; k < 4; k++) {
                            const int o = (k & 1) ? 8192 : 1152, h = k >> 1;
                            bulk_load(sbase + R1 + h * 16384 + o, img + h * (X2_IMG / 2) + o, (k & 1) ? 8192 : 7040, ZOK);
                            if (k & 1) bulk_load(sbase + R1 + h * 16384, img + h * (X2_IMG / 2), 1024, ZOK);
                            if (dz && k < 3) { const uint32_t c = clk32(); while ((int)(clk32() - c) < dz && !lds32(sbase + SACT_OFF + 4)) { } }
                        }
                    }
                }
            }
        } else if (warp == 2) {
            if (cta < 128) {
                const uint8_t* bp = reinterpret_cast<const uint8_t*>((lane & 16) ? Bim : Bre) + (cb * 128 + tc * 4 + ((lane >> 2) & 3)) * 2048 + (lane & 3) * 128;
                while (clock64() - t_start < TXT) { }
                if (elect_one()) {
                    mbar_expect_tx(XB, 32768 + 256);
                    bulk_load(sbase + GATE_OFF, gate_w + db * 64, 128, XB);
                    bulk_load(sbase + GATE_OFF + 128, gate_w + db * 64 + 512, 128, XB);
                    #pragma unroll
                    for (int i = 0; i < 8; i++) tma_load_2d(sbase + R0 + i * 4096, &mp.Xr, rc * 1024 + db * 64 + (i >> 2) * 512, (i & 3) * 32, XB);
                }
                __syncwarp();
                pf_line(bp + 1024); pf_line(bp + 1536);
                if ((cta & 63) < 12) pf_line(reinterpret_cast<const uint8_t*>(&g_img) + (cta & 63) * 4096 + lane * 128);
                while (clock64() - t_start < PFW) { }
                const uint32_t wrow = (((cta & 1) ? 128 - (cta >> 1) : (cta >> 1)) + 128 * (lane >> 1)) & 2047;
                const uint8_t* wp = reinterpret_cast<const uint8_t*>(lane & 1 ? w_i : w_r) + wrow * 1026u;
                #pragma unroll 1
                for (int k = 0; k < 9; k++) { pf_line(wp + (k < 8 ? k * 128 : 1024)); __nanosleep(200); }
                while (clock64() - t_start < PFB) { }
                #pragma unroll 1
                for (int k = 0; k < 16; k += 4) { pf_line(bp + 64 * 2048 + k * 128); __nanosleep(200); }
                const uint8_t* cp = reinterpret_cast<const uint8_t*>((lane & 16) ? Cim : Cre) + (cta * 8 + (lane & 7)) * 2048 + (lane & 8) * 32;
                #pragma unroll 1
                for (int k = 0; k < 8; k++) {
                    while (clock64() - t_start < PFC + k * PFCS) { __nanosleep(100); }
                    pf_line(cp + (k & 3) * 512 + (k >> 2) * 128);
                }
            }
        } else {
            unsigned int epoch = 0;
            if (cta >= 128) bar_sync_n(DBAR, 64);
            if (lane == 0) {
                epoch = atomicAdd(&g_ticket, 1u);
                epoch = (full ? epoch / NCTA : epoch / 130u) + 1u;
                sts32(sbase + EPO_OFF, epoch);
                mbar_arrive(EPB);
            }
            __syncwarp();
            if (cta < 128) {
                #pragma unroll 1
                for (int i = 0; i < 4; i++) {
                    bar_sync_n(HBAR + i, 160);
                    if (lane == 0) {
                        red_release(&g_cnth(i));
                        wait_counter(&g_cnth(i), 128u * epoch);
                        mbar_arrive(HOK(i));
                    }
                    __syncwarp();
                }
                if (lane == 0) {
                    mbar_expect_tx(XB, 32768);
                    #pragma unroll 1
                    for (int i = 0; i < 8; i++) { tma_load_2d(sbase + R0 + i * 4096, &mp.Xr, rc * 1024 + db * 64 + (i >> 2) * 512, (i & 3) * 32, XB); __nanosleep(150); }
                }
            } else if (cta >= 130 && lane == 0) {
                #pragma unroll 1
                for (int i = 0; i < (1 << 22); i++) {
                    __nanosleep(200);
                    if ((int)(*reinterpret_cast<volatile unsigned int*>(&g_ticket) - NCTA * epoch) >= 0) break;
                }
            }
        }
    } else if (wg >= 2) {
      if (cta < 128) {
          float2 w1, w32;
          sincospif((float)(16 * tid128() + rc) * (1.f / 1024.f), &w1.y, &w1.x);
          w32 = cmul(w1, w1); w32 = cmul(w32, w32); w32 = cmul(w32, w32); w32 = cmul(w32, w32); w32 = cmul(w32, w32);
          gen_dft(sbase + R1, tid128(), w1, wg == 2 ? make_float2(1.f, 0.f) : make_float2(w32.x, -w32.y), 4 * wg - 8, 4 * wg - 4, 0.5f);
          fence_async();
          bar_sync_n(wg, 128);
          mbar_wait(XB, 0);
          fft_p1(sbase, bars, wg - 2, rc, db, (uint32_t)t_start + P1END);
      }
      if (wg == 3) {
        asm volatile("setmaxnreg.inc.sync.aligned.u32 120;");
        {
            if (cta < 128) {
                mbar_wait(EPB, 0);
                #pragma unroll 1
                for (int half = 0; half < 2; half++) {
                    const int t1 = tid128(), ch = t1 >> 1, hf = t1 & 1, p = cb * 128 + half * 64 + ch;
                    if (half) {
                        mbar_wait(X1B(0), 0);
                        float s = 0.f;
                        #pragma unroll
                        for (int i = 0; i < 16; i++) s += __ldcg(&g_gp[(16 * rc + i) * 128 + t1]);
                        const float gv = bf16r(__fdividef(1.f, 1.f + expf(-bf16r(s))));
                        sts32(sbase + GATE_OFF + 4 * t1, pack2(gv, 1.f - gv));
                    }
                    const uint4 pm = lds128(sbase + LAM_OFF + (half * 64 + ch) * 16);
                    const uint32_t sg = (uint32_t)swp << 31;
                    float2 lam = make_float2(__uint_as_float(pm.x), __uint_as_float(pm.y ^ sg));
                    float cr = __uint_as_float(pm.z), ci = __uint_as_float(pm.w);
                    const uint4 pp = lds128(sbase + LAM_OFF + 2048 + (half * 64 + ch) * 16);
                    const float2 l16 = make_float2(__uint_as_float(pp.x), __uint_as_float(pp.y ^ sg)), l32 = make_float2(__uint_as_float(pp.z), __uint_as_float(pp.w ^ sg));
                    const float2 l64 = cmul(l32, l32), l128 = cmul(l64, l64), l256 = cmul(l128, l128);
                    const unsigned int par = lds32(sbase + EPO_OFF) & 1u;
                    if (__float_as_uint(l256.x) == 0x9e3779b9u) sts32(sbase + SACT_OFF + 4, 0u);
                    bar_sync_n(DBAR, 384);
                    uint2 ur[16], ui[16];
                    #pragma unroll
                    for (int r = 15; r >= 0; r--) { ur[r] = lds64(sbase + R0 + r * 1024 + t1 * 8); ui[r] = lds64(sbase + R0 + 16384 + r * 1024 + t1 * 8); }
                    if (cta > 999) sts32(sbase + SACT_OFF + 4, ui[0].y);
                    if (half) bar_arrive_n(KBAR, 384);
                    boundary();
                    float2 e[4], E0;
                    e[0] = make_float2(bflo(ur[15].x), bflo(ui[15].x));
                    e[1] = cfma(l16, e[0], make_float2(bfhi(ur[15].x), bfhi(ui[15].x)));
                    e[2] = cfma(l16, e[1], make_float2(bflo(ur[15].y), bflo(ui[15].y)));
                    e[3] = cfma(l16, e[2], make_float2(bfhi(ur[15].y), bfhi(ui[15].y)));
                    E0.x = __shfl_xor_sync(0xffffffffu, e[3].x, 1); E0.y = __shfl_xor_sync(0xffffffffu, e[3].y, 1);
                    const uint2* src = reinterpret_cast<const uint2*>(g_agg) + (tc - 1 - hf) * P_DIM + p;
                    const int nv = tc - hf;
                    uint2 v[8];
                    {
                        const bf2 c2 = asbf2(pack2(cr, cr)), n2 = asbf2(pack2(-cr, -cr)), s2 = asbf2(pack2(-ci, -ci));
                        #pragma unroll
                        for (int r = 15; r >= 0; r--) {
                            if (r == 8) {
                                boundary();
                                #pragma unroll
                                for (int i = 0; i < 8; i++) {
                                    v[i] = make_uint2(par, par);
                                    if (2 * i < nv) asm volatile("ld.relaxed.gpu.global.v2.u32 {%0, %1}, [%2];" : "=r"(v[i].x), "=r"(v[i].y) : "l"(src - i * 2 * P_DIM) : "memory");
                                }
                                #pragma unroll
                                for (int q = r; q >= 0; q--) asm volatile("" : "+r"(ur[q].x), "+r"(ur[q].y), "+r"(ui[q].x), "+r"(ui[q].y) :: "memory");
                            }
                            const bf2 a = asbf2(ur[r].x), b = asbf2(ui[r].x), c = asbf2(ur[r].y), d = asbf2(ui[r].y);
                            ur[r].x = asu32(__hfma2(c2, a, __hmul2(s2, b))); ui[r].x = asu32(__hfma2(n2, b, __hmul2(s2, a)));
                            ur[r].y = asu32(__hfma2(c2, c, __hmul2(s2, d))); ui[r].y = asu32(__hfma2(n2, d, __hmul2(s2, c)));
                            asm volatile("" : "+r"(ur[r].x), "+r"(ur[r].y), "+r"(ui[r].x), "+r"(ui[r].y) :: "memory");
                        }
                    }
                    __syncwarp();
                    if (lane == 0) mbar_arrive2(R0F);
                    #pragma unroll 1
                    for (int spins = 0; spins < (1 << 20); spins++) {
                        uint32_t bad = 0;
                        #pragma unroll
                        for (int i = 0; i < 8; i++) bad |= (v[i].x ^ par) | (v[i].y ^ par);
                        if (!__any_sync(0xffffffffu, bad & 1u)) break;
                        #pragma unroll
                        for (int i = 0; i < 8; i++)
                            if (2 * i < nv) asm volatile("ld.relaxed.gpu.global.v2.u32 {%0, %1}, [%2];" : "+r"(v[i].x), "+r"(v[i].y) : "l"(src - i * 2 * P_DIM) : "memory");
                    }
                    if (t1 == 0) { sts32(sbase + SACT_OFF, 1u); }
                    float2 H = make_float2(__uint_as_float(v[7].x), __uint_as_float(v[7].y));
                    #pragma unroll
                    for (int i = 6; i >= 0; i--) H = cfma(l256, H, make_float2(__uint_as_float(v[i].x), __uint_as_float(v[i].y)));
                    if (hf) H = cmul(H, l128);
                    H.x += __shfl_xor_sync(0xffffffffu, H.x, 1); H.y += __shfl_xor_sync(0xffffffffu, H.y, 1);
                    float2 st[4];
                    st[0] = hf ? cfma(l64, H, E0) : H;
                    st[1] = cfma(l16, st[0], e[0]); st[2] = cfma(l32, st[0], e[1]); st[3] = cfma(l16, cmul(l32, st[0]), e[2]);
                    const bf2 gr0 = asbf2(pack2(cr * st[0].x - ci * st[0].y, cr * st[1].x - ci * st[1].y)), gr1 = asbf2(pack2(cr * st[2].x - ci * st[2].y, cr * st[3].x - ci * st[3].y));
                    const bf2 gi0 = asbf2(pack2(-ci * st[0].x - cr * st[0].y, -ci * st[1].x - cr * st[1].y)), gi1 = asbf2(pack2(-ci * st[2].x - cr * st[2].y, -ci * st[3].x - cr * st[3].y));
                    uint2* dst = reinterpret_cast<uint2*>(g_h + (half * 16 + cb) * 1024 + tc * 64) + t1;
                    lam.y = -lam.y;
                    float2 z = lam;
                    uint32_t pw[16], tp = clk32() + warp * (PCR / 2);
                    #pragma unroll
                    for (int r = 0; r < 16; r++) {
                        pw[r] = pack2(z.x, z.y); z = cmul(z, lam);
                        const bf2 pr = __low2bfloat162(asbf2(pw[r])), pi = __high2bfloat162(asbf2(pw[r]));
                        if (!(r & 1)) pace(tp, 2 * PCR);
                        __stcg(dst + r * 65536, make_uint2(asu32(__hfma2(pr, gr0, __hfma2(pi, neg2(gi0), asbf2(ur[r].x)))), asu32(__hfma2(pr, gr1, __hfma2(pi, neg2(gi1), asbf2(ur[r].y))))));
                    }
                    bar_arrive_n(HBAR + 2 * half, 160);
                    if (t1 == 0) { sts32(sbase + SACT_OFF, 0u); }
                    #pragma unroll
                    for (int r = 0; r < 16; r++) {
                        const bf2 pr = __low2bfloat162(asbf2(pw[r])), pi = __high2bfloat162(asbf2(pw[r]));
                        if (!(r & 1)) pace(tp, 2 * PCH);
                        __stcg(dst + r * 65536 + 16384, make_uint2(asu32(__hfma2(pr, gi0, __hfma2(pi, gr0, asbf2(ui[r].x)))), asu32(__hfma2(pr, gi1, __hfma2(pi, gr1, asbf2(ui[r].y))))));
                    }
                    bar_arrive_n(HBAR + 2 * half + 1, 160);
                }
            }
        }
      } else {
        asm volatile("setmaxnreg.inc.sync.aligned.u32 144;");
        if (cta < 130) {
            fft_p2(sbase, bars, cta, w_r, w_i);
            bar_sync_n(LBAR + 2, 160);
            if (cta < 128) {
                const int j = tid128();
                if (j < 16) {
                    const uint2 d0 = __ldg(reinterpret_cast<const uint2*>(dskip) + db * 16 + j), d1 = __ldg(reinterpret_cast<const uint2*>(dskip) + db * 16 + 128 + j);
                    sts128(sbase + DSK_OFF + j * 16, d0.x, d0.y, d1.x, d1.y);
                }
                mbar_wait(HOK(2), 0);
                const float gv = bflo(lds32(sbase + GATE_OFF + 4 * j));
                gen_dft(sbase + R2, j, cis(16 * j + rc), make_float2(gv * (1.f / 1048576.f), 0.f), 0, 8, gv * (1.f / 1048576.f));
                const uint8_t* img = reinterpret_cast<const uint8_t*>(g_X2) + (8 * rc + db) * X2_IMG;
                if ((j >> 4) == 4) {
                    wait_counter(&g_cnt3, 2u * lds32(sbase + EPO_OFF));
                    const float cs = g_img.cs[0][4 * rc][0], sn = g_img.cs[0][4 * rc][1];
                    const uint4* s4 = reinterpret_cast<const uint4*>(img + ((j >> 3) & 1) * (X2_IMG / 2) + 16384) + (j & 7);
                    const uint4 a = __ldcg(s4), b = __ldcg(s4 + 64);
                    sts128(sbase + R1 + ((j >> 3) & 1) * 16384 + 1024 + (j & 7) * 16,
                           pack2(cs * bflo(a.x) - sn * bflo(b.x), cs * bfhi(a.x) - sn * bfhi(b.x)), pack2(cs * bflo(a.y) - sn * bflo(b.y), cs * bfhi(a.y) - sn * bfhi(b.y)),
                           pack2(cs * bflo(a.z) - sn * bflo(b.z), cs * bfhi(a.z) - sn * bfhi(b.z)), pack2(cs * bflo(a.w) - sn * bflo(b.w), cs * bfhi(a.w) - sn * bfhi(b.w)));
                }
                fence_async();
                mbar_arrive(ZOK);
            }
        }
      }
    } else {
        if (cta < 128) {
            {
                const int w8 = tid >> 5;
                if (w8 == 0) pf_line(((lane & 16) ? Bim : Bre) + (cb * 128 + tc * 4 + ((lane >> 2) & 3)) * 1024 + (4 + (lane & 3)) * 64);
                else if (w8 < 3) pf_line(x + (cta * 16 + (lane >> 1)) * 1024 + (2 + 2 * w8 + (lane & 1)) * 64);
            }
            float A[64];
            #pragma unroll
            for (int i = 0; i < 64; i++) A[i] = 0.f;
            gemm_main(A, sbase, wg, warp, lane, cb, tc, swp);
            const int ln = tid128() & 31, row = 64 * wg + 16 * warp + (ln >> 2);
            if (wg == 0) bar_arrive_n(TBAR, 256);
            mbar_wait(ZOK, 0);
            float om[2];
            om[0] = bfhi(lds32(sbase + GATE_OFF + 4 * row)); om[1] = bfhi(lds32(sbase + GATE_OFF + 4 * row + 32));
            wgmma_wait<0>();
            reg_fence<64>(A);
            #pragma unroll
            for (int i = 0; i < 32; i++) { const float o = om[(i >> 1) & 1], t = o * A[i], u = A[i + 32]; A[i] = fmaf(o, u, t); A[i + 32] = fmaf(-o, u, t); }
            constexpr uint32_t s16 = SBASE / 16;
            wgmma_fence();
            #pragma unroll
            for (int ks = 0; ks < 8; ks++)
                ss128<0, 1>(A, mkd(s16 + wg * 512, R2 + (ks >> 2) * 16384 + (ks & 3) * 32, 16, 1024, 1), mkd(s16, R1 + ks * 2048, 16384, 1024, 1));
            wgmma_commit();
            if (wg == 0) bar_arrive_n(TBAR + 1, 256);
            float* o = out + (size_t)(16 * row + rc) * 1024 + db * 64 + 4 * (ln & 3);
            mbar_wait(XB, 1);
            wgmma_wait<0>();
            reg_fence<64>(A);
            #pragma unroll
            for (int J = 0; J < 4; J++) {
                if (J) boundary();
                const uint4 dk = lds128(sbase + DSK_OFF + (4 * J + (ln & 3)) * 16);
                #pragma unroll
                for (int h = 0; h < 2; h++) {
                    const uint32_t xo = sbase + R0 + (row + 8 * h) * 128 + (ln & 1) * 8 + (((2 * J + ((ln >> 1) & 1)) ^ (ln >> 2)) << 4);
                    uint2 p = lds64(xo), s = lds64(xo + 16384);
                    p.x = hmul2bf(p.x, dk.x); p.y = hmul2bf(p.y, dk.y); s.x = hmul2bf(s.x, dk.z); s.y = hmul2bf(s.y, dk.w);
                    const float* a = A + 8 * J + 2 * h;
                    float4 u = make_float4(fmaf(om[h], bflo(p.x), a[0] + a[32]), fmaf(om[h], bfhi(p.x), a[1] + a[33]), fmaf(om[h], bflo(p.y), a[4] + a[36]), fmaf(om[h], bfhi(p.y), a[5] + a[37]));
                    float4 v = make_float4(fmaf(om[h], bflo(s.x), a[0] - a[32]), fmaf(om[h], bfhi(s.x), a[1] - a[33]), fmaf(om[h], bflo(s.y), a[4] - a[36]), fmaf(om[h], bfhi(s.y), a[5] - a[37]));
                    __stcs(reinterpret_cast<float4*>(o + h * 131072 + J * 16), u);
                    __stcs(reinterpret_cast<float4*>(o + h * 131072 + J * 16 + 512), v);
                }
            }
        }
    }
}

typedef CUresult (*PFN_encodeTiled_t)(CUtensorMap*, CUtensorMapDataType, cuuint32_t, void*, const cuuint64_t*, const cuuint64_t*,
                                      const cuuint32_t*, const cuuint32_t*, CUtensorMapInterleave, CUtensorMapSwizzle,
                                      CUtensorMapL2promotion, CUtensorMapFloatOOBfill);

static CUresult make_map(PFN_encodeTiled_t enc, CUtensorMap* m, int rank, const void* ptr, const cuuint64_t* dims, const cuuint64_t* strides, const cuuint32_t* box) {
    cuuint32_t es[5] = {1, 1, 1, 1, 1};
    return enc(m, CU_TENSOR_MAP_DATA_TYPE_BFLOAT16, rank, (void*)ptr, dims, strides, box, es, CU_TENSOR_MAP_INTERLEAVE_NONE, CU_TENSOR_MAP_SWIZZLE_128B,
        CU_TENSOR_MAP_L2_PROMOTION_L2_128B, CU_TENSOR_MAP_FLOAT_OOB_FILL_NONE);
}
static void make_map_2d(PFN_encodeTiled_t enc, CUtensorMap* m, const void* ptr, int rows, int cols, int box_rows) {
    cuuint64_t dims[2] = {(cuuint64_t)cols, (cuuint64_t)rows};
    cuuint64_t strides[1] = {(cuuint64_t)cols * 2};
    cuuint32_t box[2] = {64, (cuuint32_t)box_rows};
    make_map(enc, m, 2, ptr, dims, strides, box);
}

extern "C" void kernel_launch(void* const* d_in, const int* in_sizes, int n_in, void* d_out, int out_size) {
    const __nv_bfloat16* x = (const __nv_bfloat16*)d_in[0];
    const __nv_bfloat16* w_r = (const __nv_bfloat16*)d_in[1];
    const __nv_bfloat16* w_i = (const __nv_bfloat16*)d_in[2];
    const __nv_bfloat16* lam_re = (const __nv_bfloat16*)d_in[4];
    const __nv_bfloat16* lam_im = (const __nv_bfloat16*)d_in[5];
    const __nv_bfloat16* B_re = (const __nv_bfloat16*)d_in[6];
    const __nv_bfloat16* B_im = (const __nv_bfloat16*)d_in[7];
    const __nv_bfloat16* C_re = (const __nv_bfloat16*)d_in[8];
    const __nv_bfloat16* C_im = (const __nv_bfloat16*)d_in[9];
    const __nv_bfloat16* log_dt = (const __nv_bfloat16*)d_in[10];
    const __nv_bfloat16* dskip = (const __nv_bfloat16*)d_in[11];
    const __nv_bfloat16* gate_w = (const __nv_bfloat16*)d_in[12];

    static PFN_encodeTiled_t enc = nullptr;
    static Maps mp;
    static int grid = 130, swp = 0, copyB = 0;
    static void* bcopy = nullptr;
    static const void* key[7] = {nullptr, nullptr, nullptr, nullptr, nullptr, nullptr, nullptr};
    if (!enc) {
        cudaDriverEntryPointQueryResult qres;
        cudaGetDriverEntryPoint("cuTensorMapEncodeTiled", (void**)&enc, cudaEnableDefault, &qres);
        cudaFuncSetAttribute(fused_kernel<true>, cudaFuncAttributeMaxDynamicSharedMemorySize, TOT_SMEM);
        cudaFuncSetAttribute(fused_kernel<false>, cudaFuncAttributeMaxDynamicSharedMemorySize, TOT_SMEM);
        int dev = 0, nsm = 0;
        cudaGetDevice(&dev);
        cudaDeviceGetAttribute(&nsm, cudaDevAttrMultiProcessorCount, dev);
        grid = nsm == NCTA ? NCTA : 130;
    }
    if (key[0] != x || key[1] != B_re || key[2] != B_im || key[3] != C_re || key[4] != C_im || key[5] != w_r || key[6] != w_i) {
        cudaGetSymbolAddress(&bcopy, g_Bcopy);
        {
            const uintptr_t a = (uintptr_t)B_re, b = (uintptr_t)B_im;
            swp = b < a;
            cuuint64_t dims[4] = {D_DIM, 8, 2, P_DIM / 8};
            cuuint64_t strides[3] = {D_DIM * 2, (cuuint64_t)(swp ? a - b : b - a), D_DIM * 2 * 8};
            cuuint32_t box[4] = {64, 8, 2, 8};
            copyB = strides[1] == 0 || (strides[1] & 15) || strides[1] >= (1ull << 39);
            if (!copyB) copyB = make_map(enc, &mp.BB, 4, swp ? B_im : B_re, dims, strides, box) != CUDA_SUCCESS;
            if (copyB) {
                swp = 0; strides[1] = (cuuint64_t)P_DIM * D_DIM * 2;
                make_map(enc, &mp.BB, 4, bcopy, dims, strides, box);
            }
        }
        {
            cuuint64_t dims[3] = {D_DIM, S_LEN / 16, 16};
            cuuint64_t strides[2] = {D_DIM * 2 * 16, D_DIM * 2};
            cuuint32_t box[3] = {64, 8, 8};
            make_map(enc, &mp.X, 3, x, dims, strides, box);
        }
        make_map_2d(enc, &mp.Xr, x, S_LEN / 16, D_DIM * 16, 32);
        {
            cuuint64_t dims[5] = {P_DIM, 2, 4, 2, D_DIM / 16};
            cuuint64_t strides[4] = {P_DIM * 2, P_DIM * 2 * 4, P_DIM * 2 * 2, P_DIM * 2 * 16};
            cuuint32_t box[5] = {64, 2, 4, 2, 4};
            make_map(enc, &mp.Cre, 5, C_re, dims, strides, box);
            make_map(enc, &mp.Cim, 5, C_im, dims, strides, box);
        }
        for (int a = 0; a < 2; a++) {
            cuuint64_t dims[3] = {128 * 513 - 448, 8, 16};
            cuuint64_t strides[2] = {128, 128 * 513 * 2};
            cuuint32_t box[3] = {64, 8, 4};
            make_map(enc, &mp.W[a], 3, a ? w_i : w_r, dims, strides, box);
        }
        key[5] = w_r; key[6] = w_i;
        key[0] = x; key[1] = B_re; key[2] = B_im; key[3] = C_re; key[4] = C_im;
    }
    if (copyB) {
        cudaMemcpyAsync(bcopy, B_re, (size_t)P_DIM * D_DIM * 2, cudaMemcpyDeviceToDevice, cudaStreamPerThread);
        cudaMemcpyAsync((char*)bcopy + (size_t)P_DIM * D_DIM * 2, B_im, (size_t)P_DIM * D_DIM * 2, cudaMemcpyDeviceToDevice, cudaStreamPerThread);
    }
    (grid == NCTA ? fused_kernel<true> : fused_kernel<false>)<<<grid, 640, TOT_SMEM, cudaStreamPerThread>>>(x, B_re, B_im, swp, w_r, w_i, lam_re, lam_im, log_dt, dskip, gate_w,
        C_re, C_im, (float*)d_out, mp);
}
```
